```python
import torch

def _softmax(x, axis=-1):
    return torch.softmax(x, dim=axis)
def _gelu(x):
    return torch.nn.functional.gelu(x, approximate="tanh")
def _silu(x):
    return torch.nn.functional.silu(x)
def _sigmoid(x):
    return torch.sigmoid(x)
def _layernorm(x, axis=-1, eps=1e-5):
    m = x.mean(dim=axis, keepdim=True)
    v = x.var(dim=axis, keepdim=True, unbiased=False)
    return (x - m) / torch.sqrt(v + eps)
def _scatter_add(tgt, idx, src, axis=0):
    return tgt.clone().index_add_(axis, idx, src)
def _segment_sum(src, seg, n):
    out = torch.zeros((n,) + src.shape[1:], dtype=src.dtype)
    return out.index_add_(0, seg, src)
def _pad(x, pw):
    flat = tuple(v for pair in reversed(pw) for v in pair)
    return torch.nn.functional.pad(x, flat)

kernel_name = 'standalone__window_attn_swin__vision'

def setup_inputs():

    _w = (lambda a: (lambda t: t.to(torch.bfloat16) if t.is_floating_point() else t)(torch.as_tensor(a)))
    H = W = 384
    C = 192
    ws = 8
    nh = 4
    shift = ws // 2
    coords = torch.stack(torch.meshgrid(torch.arange(ws), torch.arange(ws), indexing='ij'), 0).reshape(2, -1)
    rel = coords[:, :, None] - coords[:, None, :]
    rel[0] += ws - 1
    rel[1] += ws - 1
    rel[0] *= 2 * ws - 1
    rp_idx = rel.sum(0).to(torch.int64)
    img_mask = torch.zeros((1, H, W, 1), dtype=float)
    cnt = 0
    for hs in (slice(0, H - ws), slice(H - ws, H - shift), slice(H - shift, H)):
        for vs in (slice(0, W - ws), slice(W - ws, W - shift), slice(W - shift, W)):
            img_mask[:, hs, vs, :] = cnt
            cnt += 1
    mw = img_mask.reshape(1, H // ws, ws, W // ws, ws, 1).permute(0, 1, 3, 2, 4, 5).reshape(-1, ws * ws)
    am = mw[:, :, None] - mw[:, None, :]
    attn_mask = torch.where(am != 0, -100.0, 0.0).to(float)
    return {
        "x": _w((lambda *s: torch.randn(*s, dtype=torch.bfloat16) * 1.6)(1, H, W, C)),
        "wqkv": _w((lambda *s: torch.randn(*s, dtype=torch.bfloat16) * 1.6)(C, 3 * C) * 0.02),
        "wo": _w((lambda *s: torch.randn(*s, dtype=torch.bfloat16) * 0.05)(C, C) * 0.02),
        "rpb": _w((lambda *s: torch.randn(*s, dtype=torch.bfloat16) * 0.2)((2 * ws - 1) * (2 * ws - 1), nh)),
        "rp_idx": _w(rp_idx),
        "attn_mask": _w(attn_mask),
    }

def reference(x, wqkv, wo, rpb, rp_idx, attn_mask):
    B, H, W, C = x.shape
    N = rp_idx.shape[0]
    ws = int(round(N ** 0.5))
    nh = rpb.shape[-1]
    hd = C // nh
    shift = ws // 2
    xs = torch.roll(x, (-shift, -shift), (1, 2))
    nWh = H // ws
    nWw = W // ws
    xw = (lambda x, *d: x.permute(*d))(xs.reshape(B, nWh, ws, nWw, ws, C), 0, 1, 3, 2, 4, 5).reshape(B * nWh * nWw, N, C)
    qkv = (lambda x, *d: x.permute(*d))(torch.einsum('wnc,cd->wnd', xw, wqkv).reshape(-1, N, 3, nh, hd), 2, 0, 3, 1, 4)
    q, k, v = qkv[0], qkv[1], qkv[2]
    attn = torch.einsum('whid,whjd->whij', q, k) * (hd ** -0.5)
    bias = (lambda x, *d: x.permute(*d))(rpb[rp_idx.reshape(-1)].reshape(N, N, nh), 2, 0, 1)
    attn = attn + bias[None, :, :, :]
    attn = (attn.reshape(B, nWh * nWw, nh, N, N) + attn_mask[None, :, None, :, :]).reshape(-1, nh, N, N)
    attn = _softmax(attn, axis=-1)
    out = (lambda x, *d: x.permute(*d))(torch.einsum('whij,whjd->whid', attn, v), 0, 2, 1, 3).reshape(-1, N, C)
    out = torch.einsum('wnc,cd->wnd', out, wo)
    out = (lambda x, *d: x.permute(*d))(out.reshape(B, nWh, nWw, ws, ws, C), 0, 1, 3, 2, 4, 5).reshape(B, H, W, C)
    return torch.roll(out, (shift, shift), (1, 2))
```

```cpp
#include <cuda_runtime.h>
#include <cuda_bf16.h>
#include <cuda.h>
#include <stdint.h>

namespace swin {

constexpr int IMG = 384;
constexpr int CH = 192;
constexpr int NWIN = 48 * 48;
constexpr int NWG = 3;
constexpr int NTHREADS = NWG * 128;
#define PF_DIST_ 1
constexpr int PF_DIST = PF_DIST_;

constexpr uint32_t SM_WQKV = 0;
constexpr uint32_t W_PART = 3 * 192 * 32;
constexpr uint32_t WQKV_HEAD = 3 * W_PART;
constexpr uint32_t SM_WO = 2 * WQKV_HEAD;
constexpr uint32_t WO_HALF = 6 * 96 * 32;
constexpr uint32_t SM_X = SM_WO + 2 * WO_HALF;
constexpr uint32_t X_QUAD = 3 * 16 * 128;
constexpr uint32_t SM_WG = SM_X + 4 * X_QUAD;
constexpr uint32_t OFF_K1 = 0;
constexpr uint32_t OFF_V0 = 6144;
constexpr uint32_t OFF_ONES = OFF_V0 + 6144;
constexpr uint32_t OFF_K0 = OFF_ONES + 1024;
constexpr uint32_t WG_BYTES = OFF_K0 + 6144;
constexpr uint32_t SM_BAR = SM_WG + NWG * WG_BYTES;
constexpr uint32_t SM_TOTAL = SM_BAR + 8 * (12 + 12 + 1);
static_assert(SM_X % 1024 == 0, "X stage must be swizzle-atom aligned");
static_assert(SM_TOTAL <= 232448, "shared memory budget");

constexpr float LOG2E = 1.4426950408889634f;
constexpr float QSCALE = 0.14433756729740643f * LOG2E;
constexpr uint32_t LOG2E_BF16X2 = 0x3FB93FB9u;

constexpr uint32_t W_IMG = SM_X;
__device__ __align__(128) uint4 g_wimg[2][W_IMG / 16];
__device__ uint4 g_bias[2][1024];

template <int TB> __device__ __forceinline__ void wgmma_rs_n56_init(float (&d)[28], uint32_t a0, uint32_t a1, uint32_t a2, uint32_t a3, uint64_t desc) {
  asm volatile("wgmma.mma_async.sync.aligned.m64n56k16.f32.bf16.bf16 "
    "{%0, %1, %2, %3, %4, %5, %6, %7, %8, %9, %10, %11, %12, %13, %14, %15, %16, %17, %18, %19, %20, %21, %22, %23, %24, %25, %26, %27}, "
    "{%28, %29, %30, %31}, %32, 0, 1, 1, %33;"
    : "=f"(d[0]), "=f"(d[1]), "=f"(d[2]), "=f"(d[3]), "=f"(d[4]), "=f"(d[5]), "=f"(d[6]), "=f"(d[7]), "=f"(d[8]), "=f"(d[9]), "=f"(d[10]), "=f"(d[11]), "=f"(d[12]), "=f"(d[13]), "=f"(d[14]), "=f"(d[15]), "=f"(d[16]), "=f"(d[17]), "=f"(d[18]), "=f"(d[19]), "=f"(d[20]), "=f"(d[21]), "=f"(d[22]), "=f"(d[23]), "=f"(d[24]), "=f"(d[25]), "=f"(d[26]), "=f"(d[27])
    : "r"(a0), "r"(a1), "r"(a2), "r"(a3), "l"(desc), "n"(TB));
}
template <int TB> __device__ __forceinline__ void wgmma_rs_n56(float (&d)[28], uint32_t a0, uint32_t a1, uint32_t a2, uint32_t a3, uint64_t desc) {
  asm volatile("wgmma.mma_async.sync.aligned.m64n56k16.f32.bf16.bf16 "
    "{%0, %1, %2, %3, %4, %5, %6, %7, %8, %9, %10, %11, %12, %13, %14, %15, %16, %17, %18, %19, %20, %21, %22, %23, %24, %25, %26, %27}, "
    "{%28, %29, %30, %31}, %32, 1, 1, 1, %33;"
    : "+f"(d[0]), "+f"(d[1]), "+f"(d[2]), "+f"(d[3]), "+f"(d[4]), "+f"(d[5]), "+f"(d[6]), "+f"(d[7]), "+f"(d[8]), "+f"(d[9]), "+f"(d[10]), "+f"(d[11]), "+f"(d[12]), "+f"(d[13]), "+f"(d[14]), "+f"(d[15]), "+f"(d[16]), "+f"(d[17]), "+f"(d[18]), "+f"(d[19]), "+f"(d[20]), "+f"(d[21]), "+f"(d[22]), "+f"(d[23]), "+f"(d[24]), "+f"(d[25]), "+f"(d[26]), "+f"(d[27])
    : "r"(a0), "r"(a1), "r"(a2), "r"(a3), "l"(desc), "n"(TB));
}
template <int TB> __device__ __forceinline__ void wgmma_rs_n64_init(float (&d)[32], uint32_t a0, uint32_t a1, uint32_t a2, uint32_t a3, uint64_t desc) {
  asm volatile("wgmma.mma_async.sync.aligned.m64n64k16.f32.bf16.bf16 "
    "{%0, %1, %2, %3, %4, %5, %6, %7, %8, %9, %10, %11, %12, %13, %14, %15, %16, %17, %18, %19, %20, %21, %22, %23, %24, %25, %26, %27, %28, %29, %30, %31}, "
    "{%32, %33, %34, %35}, %36, 0, 1, 1, %37;"
    : "=f"(d[0]), "=f"(d[1]), "=f"(d[2]), "=f"(d[3]), "=f"(d[4]), "=f"(d[5]), "=f"(d[6]), "=f"(d[7]), "=f"(d[8]), "=f"(d[9]), "=f"(d[10]), "=f"(d[11]), "=f"(d[12]), "=f"(d[13]), "=f"(d[14]), "=f"(d[15]), "=f"(d[16]), "=f"(d[17]), "=f"(d[18]), "=f"(d[19]), "=f"(d[20]), "=f"(d[21]), "=f"(d[22]), "=f"(d[23]), "=f"(d[24]), "=f"(d[25]), "=f"(d[26]), "=f"(d[27]), "=f"(d[28]), "=f"(d[29]), "=f"(d[30]), "=f"(d[31])
    : "r"(a0), "r"(a1), "r"(a2), "r"(a3), "l"(desc), "n"(TB));
}
template <int TB> __device__ __forceinline__ void wgmma_rs_n64(float (&d)[32], uint32_t a0, uint32_t a1, uint32_t a2, uint32_t a3, uint64_t desc) {
  asm volatile("wgmma.mma_async.sync.aligned.m64n64k16.f32.bf16.bf16 "
    "{%0, %1, %2, %3, %4, %5, %6, %7, %8, %9, %10, %11, %12, %13, %14, %15, %16, %17, %18, %19, %20, %21, %22, %23, %24, %25, %26, %27, %28, %29, %30, %31}, "
    "{%32, %33, %34, %35}, %36, 1, 1, 1, %37;"
    : "+f"(d[0]), "+f"(d[1]), "+f"(d[2]), "+f"(d[3]), "+f"(d[4]), "+f"(d[5]), "+f"(d[6]), "+f"(d[7]), "+f"(d[8]), "+f"(d[9]), "+f"(d[10]), "+f"(d[11]), "+f"(d[12]), "+f"(d[13]), "+f"(d[14]), "+f"(d[15]), "+f"(d[16]), "+f"(d[17]), "+f"(d[18]), "+f"(d[19]), "+f"(d[20]), "+f"(d[21]), "+f"(d[22]), "+f"(d[23]), "+f"(d[24]), "+f"(d[25]), "+f"(d[26]), "+f"(d[27]), "+f"(d[28]), "+f"(d[29]), "+f"(d[30]), "+f"(d[31])
    : "r"(a0), "r"(a1), "r"(a2), "r"(a3), "l"(desc), "n"(TB));
}
template <int TB> __device__ __forceinline__ void wgmma_rs_n64_zero(float (&d)[32], uint32_t a0, uint32_t a1, uint32_t a2, uint32_t a3, uint64_t desc) {
  asm volatile("wgmma.mma_async.sync.aligned.m64n64k16.f32.bf16.bf16 "
    "{%0, %1, %2, %3, %4, %5, %6, %7, %8, %9, %10, %11, %12, %13, %14, %15, %16, %17, %18, %19, %20, %21, %22, %23, %24, %25, %26, %27, %28, %29, %30, %31}, "
    "{%32, %33, %34, %35}, %36, 0, 1, 1, %37;"
    : "+f"(d[0]), "+f"(d[1]), "+f"(d[2]), "+f"(d[3]), "+f"(d[4]), "+f"(d[5]), "+f"(d[6]), "+f"(d[7]), "+f"(d[8]), "+f"(d[9]), "+f"(d[10]), "+f"(d[11]), "+f"(d[12]), "+f"(d[13]), "+f"(d[14]), "+f"(d[15]), "+f"(d[16]), "+f"(d[17]), "+f"(d[18]), "+f"(d[19]), "+f"(d[20]), "+f"(d[21]), "+f"(d[22]), "+f"(d[23]), "+f"(d[24]), "+f"(d[25]), "+f"(d[26]), "+f"(d[27]), "+f"(d[28]), "+f"(d[29]), "+f"(d[30]), "+f"(d[31])
    : "r"(a0), "r"(a1), "r"(a2), "r"(a3), "l"(desc), "n"(TB));
}
template <int TB> __device__ __forceinline__ void wgmma_rs_n80_init(float (&d)[40], uint32_t a0, uint32_t a1, uint32_t a2, uint32_t a3, uint64_t desc) {
  asm volatile("wgmma.mma_async.sync.aligned.m64n80k16.f32.bf16.bf16 "
    "{%0, %1, %2, %3, %4, %5, %6, %7, %8, %9, %10, %11, %12, %13, %14, %15, %16, %17, %18, %19, %20, %21, %22, %23, %24, %25, %26, %27, %28, %29, %30, %31, %32, %33, %34, %35, %36, %37, %38, %39}, "
    "{%40, %41, %42, %43}, %44, 0, 1, 1, %45;"
    : "=f"(d[0]), "=f"(d[1]), "=f"(d[2]), "=f"(d[3]), "=f"(d[4]), "=f"(d[5]), "=f"(d[6]), "=f"(d[7]), "=f"(d[8]), "=f"(d[9]), "=f"(d[10]), "=f"(d[11]), "=f"(d[12]), "=f"(d[13]), "=f"(d[14]), "=f"(d[15]), "=f"(d[16]), "=f"(d[17]), "=f"(d[18]), "=f"(d[19]), "=f"(d[20]), "=f"(d[21]), "=f"(d[22]), "=f"(d[23]), "=f"(d[24]), "=f"(d[25]), "=f"(d[26]), "=f"(d[27]), "=f"(d[28]), "=f"(d[29]), "=f"(d[30]), "=f"(d[31]), "=f"(d[32]), "=f"(d[33]), "=f"(d[34]), "=f"(d[35]), "=f"(d[36]), "=f"(d[37]), "=f"(d[38]), "=f"(d[39])
    : "r"(a0), "r"(a1), "r"(a2), "r"(a3), "l"(desc), "n"(TB));
}
template <int TB> __device__ __forceinline__ void wgmma_rs_n80(float (&d)[40], uint32_t a0, uint32_t a1, uint32_t a2, uint32_t a3, uint64_t desc) {
  asm volatile("wgmma.mma_async.sync.aligned.m64n80k16.f32.bf16.bf16 "
    "{%0, %1, %2, %3, %4, %5, %6, %7, %8, %9, %10, %11, %12, %13, %14, %15, %16, %17, %18, %19, %20, %21, %22, %23, %24, %25, %26, %27, %28, %29, %30, %31, %32, %33, %34, %35, %36, %37, %38, %39}, "
    "{%40, %41, %42, %43}, %44, 1, 1, 1, %45;"
    : "+f"(d[0]), "+f"(d[1]), "+f"(d[2]), "+f"(d[3]), "+f"(d[4]), "+f"(d[5]), "+f"(d[6]), "+f"(d[7]), "+f"(d[8]), "+f"(d[9]), "+f"(d[10]), "+f"(d[11]), "+f"(d[12]), "+f"(d[13]), "+f"(d[14]), "+f"(d[15]), "+f"(d[16]), "+f"(d[17]), "+f"(d[18]), "+f"(d[19]), "+f"(d[20]), "+f"(d[21]), "+f"(d[22]), "+f"(d[23]), "+f"(d[24]), "+f"(d[25]), "+f"(d[26]), "+f"(d[27]), "+f"(d[28]), "+f"(d[29]), "+f"(d[30]), "+f"(d[31]), "+f"(d[32]), "+f"(d[33]), "+f"(d[34]), "+f"(d[35]), "+f"(d[36]), "+f"(d[37]), "+f"(d[38]), "+f"(d[39])
    : "r"(a0), "r"(a1), "r"(a2), "r"(a3), "l"(desc), "n"(TB));
}
template <int TB> __device__ __forceinline__ void wgmma_rs_n80_zero(float (&d)[40], uint32_t a0, uint32_t a1, uint32_t a2, uint32_t a3, uint64_t desc) {
  asm volatile("wgmma.mma_async.sync.aligned.m64n80k16.f32.bf16.bf16 "
    "{%0, %1, %2, %3, %4, %5, %6, %7, %8, %9, %10, %11, %12, %13, %14, %15, %16, %17, %18, %19, %20, %21, %22, %23, %24, %25, %26, %27, %28, %29, %30, %31, %32, %33, %34, %35, %36, %37, %38, %39}, "
    "{%40, %41, %42, %43}, %44, 0, 1, 1, %45;"
    : "+f"(d[0]), "+f"(d[1]), "+f"(d[2]), "+f"(d[3]), "+f"(d[4]), "+f"(d[5]), "+f"(d[6]), "+f"(d[7]), "+f"(d[8]), "+f"(d[9]), "+f"(d[10]), "+f"(d[11]), "+f"(d[12]), "+f"(d[13]), "+f"(d[14]), "+f"(d[15]), "+f"(d[16]), "+f"(d[17]), "+f"(d[18]), "+f"(d[19]), "+f"(d[20]), "+f"(d[21]), "+f"(d[22]), "+f"(d[23]), "+f"(d[24]), "+f"(d[25]), "+f"(d[26]), "+f"(d[27]), "+f"(d[28]), "+f"(d[29]), "+f"(d[30]), "+f"(d[31]), "+f"(d[32]), "+f"(d[33]), "+f"(d[34]), "+f"(d[35]), "+f"(d[36]), "+f"(d[37]), "+f"(d[38]), "+f"(d[39])
    : "r"(a0), "r"(a1), "r"(a2), "r"(a3), "l"(desc), "n"(TB));
}
template <int TB> __device__ __forceinline__ void wgmma_rs_n96_init(float (&d)[48], uint32_t a0, uint32_t a1, uint32_t a2, uint32_t a3, uint64_t desc) {
  asm volatile("wgmma.mma_async.sync.aligned.m64n96k16.f32.bf16.bf16 "
    "{%0, %1, %2, %3, %4, %5, %6, %7, %8, %9, %10, %11, %12, %13, %14, %15, %16, %17, %18, %19, %20, %21, %22, %23, %24, %25, %26, %27, %28, %29, %30, %31, %32, %33, %34, %35, %36, %37, %38, %39, %40, %41, %42, %43, %44, %45, %46, %47}, "
    "{%48, %49, %50, %51}, %52, 0, 1, 1, %53;"
    : "=f"(d[0]), "=f"(d[1]), "=f"(d[2]), "=f"(d[3]), "=f"(d[4]), "=f"(d[5]), "=f"(d[6]), "=f"(d[7]), "=f"(d[8]), "=f"(d[9]), "=f"(d[10]), "=f"(d[11]), "=f"(d[12]), "=f"(d[13]), "=f"(d[14]), "=f"(d[15]), "=f"(d[16]), "=f"(d[17]), "=f"(d[18]), "=f"(d[19]), "=f"(d[20]), "=f"(d[21]), "=f"(d[22]), "=f"(d[23]), "=f"(d[24]), "=f"(d[25]), "=f"(d[26]), "=f"(d[27]), "=f"(d[28]), "=f"(d[29]), "=f"(d[30]), "=f"(d[31]), "=f"(d[32]), "=f"(d[33]), "=f"(d[34]), "=f"(d[35]), "=f"(d[36]), "=f"(d[37]), "=f"(d[38]), "=f"(d[39]), "=f"(d[40]), "=f"(d[41]), "=f"(d[42]), "=f"(d[43]), "=f"(d[44]), "=f"(d[45]), "=f"(d[46]), "=f"(d[47])
    : "r"(a0), "r"(a1), "r"(a2), "r"(a3), "l"(desc), "n"(TB));
}
template <int TB> __device__ __forceinline__ void wgmma_rs_n96(float (&d)[48], uint32_t a0, uint32_t a1, uint32_t a2, uint32_t a3, uint64_t desc) {
  asm volatile("wgmma.mma_async.sync.aligned.m64n96k16.f32.bf16.bf16 "
    "{%0, %1, %2, %3, %4, %5, %6, %7, %8, %9, %10, %11, %12, %13, %14, %15, %16, %17, %18, %19, %20, %21, %22, %23, %24, %25, %26, %27, %28, %29, %30, %31, %32, %33, %34, %35, %36, %37, %38, %39, %40, %41, %42, %43, %44, %45, %46, %47}, "
    "{%48, %49, %50, %51}, %52, 1, 1, 1, %53;"
    : "+f"(d[0]), "+f"(d[1]), "+f"(d[2]), "+f"(d[3]), "+f"(d[4]), "+f"(d[5]), "+f"(d[6]), "+f"(d[7]), "+f"(d[8]), "+f"(d[9]), "+f"(d[10]), "+f"(d[11]), "+f"(d[12]), "+f"(d[13]), "+f"(d[14]), "+f"(d[15]), "+f"(d[16]), "+f"(d[17]), "+f"(d[18]), "+f"(d[19]), "+f"(d[20]), "+f"(d[21]), "+f"(d[22]), "+f"(d[23]), "+f"(d[24]), "+f"(d[25]), "+f"(d[26]), "+f"(d[27]), "+f"(d[28]), "+f"(d[29]), "+f"(d[30]), "+f"(d[31]), "+f"(d[32]), "+f"(d[33]), "+f"(d[34]), "+f"(d[35]), "+f"(d[36]), "+f"(d[37]), "+f"(d[38]), "+f"(d[39]), "+f"(d[40]), "+f"(d[41]), "+f"(d[42]), "+f"(d[43]), "+f"(d[44]), "+f"(d[45]), "+f"(d[46]), "+f"(d[47])
    : "r"(a0), "r"(a1), "r"(a2), "r"(a3), "l"(desc), "n"(TB));
}
template <int TB> __device__ __forceinline__ void wgmma_rs_n96_zero(float (&d)[48], uint32_t a0, uint32_t a1, uint32_t a2, uint32_t a3, uint64_t desc) {
  asm volatile("wgmma.mma_async.sync.aligned.m64n96k16.f32.bf16.bf16 "
    "{%0, %1, %2, %3, %4, %5, %6, %7, %8, %9, %10, %11, %12, %13, %14, %15, %16, %17, %18, %19, %20, %21, %22, %23, %24, %25, %26, %27, %28, %29, %30, %31, %32, %33, %34, %35, %36, %37, %38, %39, %40, %41, %42, %43, %44, %45, %46, %47}, "
    "{%48, %49, %50, %51}, %52, 0, 1, 1, %53;"
    : "+f"(d[0]), "+f"(d[1]), "+f"(d[2]), "+f"(d[3]), "+f"(d[4]), "+f"(d[5]), "+f"(d[6]), "+f"(d[7]), "+f"(d[8]), "+f"(d[9]), "+f"(d[10]), "+f"(d[11]), "+f"(d[12]), "+f"(d[13]), "+f"(d[14]), "+f"(d[15]), "+f"(d[16]), "+f"(d[17]), "+f"(d[18]), "+f"(d[19]), "+f"(d[20]), "+f"(d[21]), "+f"(d[22]), "+f"(d[23]), "+f"(d[24]), "+f"(d[25]), "+f"(d[26]), "+f"(d[27]), "+f"(d[28]), "+f"(d[29]), "+f"(d[30]), "+f"(d[31]), "+f"(d[32]), "+f"(d[33]), "+f"(d[34]), "+f"(d[35]), "+f"(d[36]), "+f"(d[37]), "+f"(d[38]), "+f"(d[39]), "+f"(d[40]), "+f"(d[41]), "+f"(d[42]), "+f"(d[43]), "+f"(d[44]), "+f"(d[45]), "+f"(d[46]), "+f"(d[47])
    : "r"(a0), "r"(a1), "r"(a2), "r"(a3), "l"(desc), "n"(TB));
}
template <int TB> __device__ __forceinline__ void wgmma_rs_n144_init(float (&d)[72], uint32_t a0, uint32_t a1, uint32_t a2, uint32_t a3, uint64_t desc) {
  asm volatile("wgmma.mma_async.sync.aligned.m64n144k16.f32.bf16.bf16 "
    "{%0, %1, %2, %3, %4, %5, %6, %7, %8, %9, %10, %11, %12, %13, %14, %15, %16, %17, %18, %19, %20, %21, %22, %23, %24, %25, %26, %27, %28, %29, %30, %31, %32, %33, %34, %35, %36, %37, %38, %39, %40, %41, %42, %43, %44, %45, %46, %47, %48, %49, %50, %51, %52, %53, %54, %55, %56, %57, %58, %59, %60, %61, %62, %63, %64, %65, %66, %67, %68, %69, %70, %71}, "
    "{%72, %73, %74, %75}, %76, 0, 1, 1, %77;"
    : "=f"(d[0]), "=f"(d[1]), "=f"(d[2]), "=f"(d[3]), "=f"(d[4]), "=f"(d[5]), "=f"(d[6]), "=f"(d[7]), "=f"(d[8]), "=f"(d[9]), "=f"(d[10]), "=f"(d[11]), "=f"(d[12]), "=f"(d[13]), "=f"(d[14]), "=f"(d[15]), "=f"(d[16]), "=f"(d[17]), "=f"(d[18]), "=f"(d[19]), "=f"(d[20]), "=f"(d[21]), "=f"(d[22]), "=f"(d[23]), "=f"(d[24]), "=f"(d[25]), "=f"(d[26]), "=f"(d[27]), "=f"(d[28]), "=f"(d[29]), "=f"(d[30]), "=f"(d[31]), "=f"(d[32]), "=f"(d[33]), "=f"(d[34]), "=f"(d[35]), "=f"(d[36]), "=f"(d[37]), "=f"(d[38]), "=f"(d[39]), "=f"(d[40]), "=f"(d[41]), "=f"(d[42]), "=f"(d[43]), "=f"(d[44]), "=f"(d[45]), "=f"(d[46]), "=f"(d[47]), "=f"(d[48]), "=f"(d[49]), "=f"(d[50]), "=f"(d[51]), "=f"(d[52]), "=f"(d[53]), "=f"(d[54]), "=f"(d[55]), "=f"(d[56]), "=f"(d[57]), "=f"(d[58]), "=f"(d[59]), "=f"(d[60]), "=f"(d[61]), "=f"(d[62]), "=f"(d[63]), "=f"(d[64]), "=f"(d[65]), "=f"(d[66]), "=f"(d[67]), "=f"(d[68]), "=f"(d[69]), "=f"(d[70]), "=f"(d[71])
    : "r"(a0), "r"(a1), "r"(a2), "r"(a3), "l"(desc), "n"(TB));
}
template <int TB> __device__ __forceinline__ void wgmma_rs_n144(float (&d)[72], uint32_t a0, uint32_t a1, uint32_t a2, uint32_t a3, uint64_t desc) {
  asm volatile("wgmma.mma_async.sync.aligned.m64n144k16.f32.bf16.bf16 "
    "{%0, %1, %2, %3, %4, %5, %6, %7, %8, %9, %10, %11, %12, %13, %14, %15, %16, %17, %18, %19, %20, %21, %22, %23, %24, %25, %26, %27, %28, %29, %30, %31, %32, %33, %34, %35, %36, %37, %38, %39, %40, %41, %42, %43, %44, %45, %46, %47, %48, %49, %50, %51, %52, %53, %54, %55, %56, %57, %58, %59, %60, %61, %62, %63, %64, %65, %66, %67, %68, %69, %70, %71}, "
    "{%72, %73, %74, %75}, %76, 1, 1, 1, %77;"
    : "+f"(d[0]), "+f"(d[1]), "+f"(d[2]), "+f"(d[3]), "+f"(d[4]), "+f"(d[5]), "+f"(d[6]), "+f"(d[7]), "+f"(d[8]), "+f"(d[9]), "+f"(d[10]), "+f"(d[11]), "+f"(d[12]), "+f"(d[13]), "+f"(d[14]), "+f"(d[15]), "+f"(d[16]), "+f"(d[17]), "+f"(d[18]), "+f"(d[19]), "+f"(d[20]), "+f"(d[21]), "+f"(d[22]), "+f"(d[23]), "+f"(d[24]), "+f"(d[25]), "+f"(d[26]), "+f"(d[27]), "+f"(d[28]), "+f"(d[29]), "+f"(d[30]), "+f"(d[31]), "+f"(d[32]), "+f"(d[33]), "+f"(d[34]), "+f"(d[35]), "+f"(d[36]), "+f"(d[37]), "+f"(d[38]), "+f"(d[39]), "+f"(d[40]), "+f"(d[41]), "+f"(d[42]), "+f"(d[43]), "+f"(d[44]), "+f"(d[45]), "+f"(d[46]), "+f"(d[47]), "+f"(d[48]), "+f"(d[49]), "+f"(d[50]), "+f"(d[51]), "+f"(d[52]), "+f"(d[53]), "+f"(d[54]), "+f"(d[55]), "+f"(d[56]), "+f"(d[57]), "+f"(d[58]), "+f"(d[59]), "+f"(d[60]), "+f"(d[61]), "+f"(d[62]), "+f"(d[63]), "+f"(d[64]), "+f"(d[65]), "+f"(d[66]), "+f"(d[67]), "+f"(d[68]), "+f"(d[69]), "+f"(d[70]), "+f"(d[71])
    : "r"(a0), "r"(a1), "r"(a2), "r"(a3), "l"(desc), "n"(TB));
}
template <int TA, int TB> __device__ __forceinline__ void wgmma_ss_n96_init(float (&d)[48], uint64_t desca, uint64_t descb) {
  asm volatile("wgmma.mma_async.sync.aligned.m64n96k16.f32.bf16.bf16 "
    "{%0, %1, %2, %3, %4, %5, %6, %7, %8, %9, %10, %11, %12, %13, %14, %15, %16, %17, %18, %19, %20, %21, %22, %23, %24, %25, %26, %27, %28, %29, %30, %31, %32, %33, %34, %35, %36, %37, %38, %39, %40, %41, %42, %43, %44, %45, %46, %47}, "
    "%48, %49, 0, 1, 1, %50, %51;"
    : "=f"(d[0]), "=f"(d[1]), "=f"(d[2]), "=f"(d[3]), "=f"(d[4]), "=f"(d[5]), "=f"(d[6]), "=f"(d[7]), "=f"(d[8]), "=f"(d[9]), "=f"(d[10]), "=f"(d[11]), "=f"(d[12]), "=f"(d[13]), "=f"(d[14]), "=f"(d[15]), "=f"(d[16]), "=f"(d[17]), "=f"(d[18]), "=f"(d[19]), "=f"(d[20]), "=f"(d[21]), "=f"(d[22]), "=f"(d[23]), "=f"(d[24]), "=f"(d[25]), "=f"(d[26]), "=f"(d[27]), "=f"(d[28]), "=f"(d[29]), "=f"(d[30]), "=f"(d[31]), "=f"(d[32]), "=f"(d[33]), "=f"(d[34]), "=f"(d[35]), "=f"(d[36]), "=f"(d[37]), "=f"(d[38]), "=f"(d[39]), "=f"(d[40]), "=f"(d[41]), "=f"(d[42]), "=f"(d[43]), "=f"(d[44]), "=f"(d[45]), "=f"(d[46]), "=f"(d[47])
    : "l"(desca), "l"(descb), "n"(TA), "n"(TB));
}
template <int TA, int TB> __device__ __forceinline__ void wgmma_ss_n96(float (&d)[48], uint64_t desca, uint64_t descb) {
  asm volatile("wgmma.mma_async.sync.aligned.m64n96k16.f32.bf16.bf16 "
    "{%0, %1, %2, %3, %4, %5, %6, %7, %8, %9, %10, %11, %12, %13, %14, %15, %16, %17, %18, %19, %20, %21, %22, %23, %24, %25, %26, %27, %28, %29, %30, %31, %32, %33, %34, %35, %36, %37, %38, %39, %40, %41, %42, %43, %44, %45, %46, %47}, "
    "%48, %49, 1, 1, 1, %50, %51;"
    : "+f"(d[0]), "+f"(d[1]), "+f"(d[2]), "+f"(d[3]), "+f"(d[4]), "+f"(d[5]), "+f"(d[6]), "+f"(d[7]), "+f"(d[8]), "+f"(d[9]), "+f"(d[10]), "+f"(d[11]), "+f"(d[12]), "+f"(d[13]), "+f"(d[14]), "+f"(d[15]), "+f"(d[16]), "+f"(d[17]), "+f"(d[18]), "+f"(d[19]), "+f"(d[20]), "+f"(d[21]), "+f"(d[22]), "+f"(d[23]), "+f"(d[24]), "+f"(d[25]), "+f"(d[26]), "+f"(d[27]), "+f"(d[28]), "+f"(d[29]), "+f"(d[30]), "+f"(d[31]), "+f"(d[32]), "+f"(d[33]), "+f"(d[34]), "+f"(d[35]), "+f"(d[36]), "+f"(d[37]), "+f"(d[38]), "+f"(d[39]), "+f"(d[40]), "+f"(d[41]), "+f"(d[42]), "+f"(d[43]), "+f"(d[44]), "+f"(d[45]), "+f"(d[46]), "+f"(d[47])
    : "l"(desca), "l"(descb), "n"(TA), "n"(TB));
}

__device__ __forceinline__ void wg_fence() { asm volatile("wgmma.fence.sync.aligned;" ::: "memory"); }
__device__ __forceinline__ void wg_commit() { asm volatile("wgmma.commit_group.sync.aligned;" ::: "memory"); }
template <int N> __device__ __forceinline__ void wg_wait() {
  asm volatile("wgmma.wait_group.sync.aligned %0;" ::"n"(N) : "memory");
}
template <int N> __device__ __forceinline__ void pin(float (&a)[N]) {
#pragma unroll
  for (int i = 0; i < N; i++) asm volatile("" : "+f"(a[i])::"memory");
}
__device__ __forceinline__ uint64_t make_desc(uint32_t addr, uint32_t lbo, uint32_t sbo) {
  uint32_t lo = ((addr & 0x3FFFF) >> 4) | ((lbo >> 4) << 16);
  uint32_t hi = sbo >> 4;
  return ((uint64_t)hi << 32) | lo;
}
__device__ __forceinline__ uint64_t make_desc_sw32(uint32_t addr, uint32_t lbo, uint32_t sbo) {
  return make_desc(addr, lbo, sbo) | (3ull << 62);
}
__device__ __forceinline__ uint64_t make_desc_sw64(uint32_t addr, uint32_t sbo) {
  return make_desc(addr, 16, sbo) | (2ull << 62);
}
__device__ __forceinline__ uint64_t desc_add(uint64_t d, uint32_t bytes) { return d + (bytes >> 4); }

__device__ __forceinline__ uint32_t pack_bf16(float lo, float hi) {
  uint32_t r;
  asm("cvt.rn.bf16x2.f32 %0, %1, %2;" : "=r"(r) : "f"(hi), "f"(lo));
  return r;
}
__device__ __forceinline__ uint32_t pack_bf16_v(float lo, float hi) {
  uint32_t r;
  asm volatile("cvt.rn.bf16x2.f32 %0, %1, %2;" : "=r"(r) : "f"(hi), "f"(lo));
  return r;
}
__device__ __forceinline__ uint32_t bf2_add(uint32_t a, uint32_t b) {
  uint32_t r; asm("add.rn.bf16x2 %0, %1, %2;" : "=r"(r) : "r"(a), "r"(b)); return r;
}
__device__ __forceinline__ uint32_t bf2_sub(uint32_t a, uint32_t b) {
  uint32_t r; asm("sub.rn.bf16x2 %0, %1, %2;" : "=r"(r) : "r"(a), "r"(b)); return r;
}
__device__ __forceinline__ uint32_t bf2_fma(uint32_t a, uint32_t b, uint32_t c) {
  uint32_t r; asm("fma.rn.bf16x2 %0, %1, %2, %3;" : "=r"(r) : "r"(a), "r"(b), "r"(c)); return r;
}
__device__ __forceinline__ uint32_t bf2_max(uint32_t a, uint32_t b) {
  uint32_t r; asm("max.bf16x2 %0, %1, %2;" : "=r"(r) : "r"(a), "r"(b)); return r;
}
__device__ __forceinline__ uint32_t bf2_ex2(uint32_t a) {
  uint32_t r; asm("ex2.approx.ftz.bf16x2 %0, %1;" : "=r"(r) : "r"(a)); return r;
}
__device__ __forceinline__ float rcp_approx(float a) {
  float r; asm("rcp.approx.ftz.f32 %0, %1;" : "=f"(r) : "f"(a)); return r;
}
__device__ __forceinline__ uint4 ldg_stream(const void* p) {
  uint4 v;
  asm volatile("ld.global.L1::no_allocate.v4.b32 {%0,%1,%2,%3}, [%4];"
               : "=r"(v.x), "=r"(v.y), "=r"(v.z), "=r"(v.w) : "l"(p));
  return v;
}
__device__ __forceinline__ uint4 ldg_cached(const void* p) {
  uint4 v;
  asm volatile("ld.global.nc.v4.b32 {%0,%1,%2,%3}, [%4];"
               : "=r"(v.x), "=r"(v.y), "=r"(v.z), "=r"(v.w) : "l"(p));
  return v;
}
__device__ __forceinline__ uint4 lds128(uint32_t addr) {
  uint4 v;
  asm volatile("ld.shared.v4.b32 {%0,%1,%2,%3}, [%4];" : "=r"(v.x), "=r"(v.y), "=r"(v.z), "=r"(v.w) : "r"(addr) : "memory");
  return v;
}
__device__ __forceinline__ void ldsm_x4(uint32_t addr, uint4& v) {
  asm volatile("ldmatrix.sync.aligned.m8n8.x4.shared.b16 {%0,%1,%2,%3}, [%4];"
               : "=r"(v.x), "=r"(v.y), "=r"(v.z), "=r"(v.w) : "r"(addr) : "memory");
}
__device__ __forceinline__ void tma_load_4d(uint32_t dst, const CUtensorMap* map, uint32_t bar, int c1, int c2) {
  asm volatile("cp.async.bulk.tensor.4d.shared::cluster.global.mbarrier::complete_tx::bytes [%0], [%1, {%3, %4, %5, %3}], [%2];"
               ::"r"(dst), "l"(map), "r"(bar), "r"(0), "r"(c1), "r"(c2) : "memory");
}
__device__ __forceinline__ void tma_prefetch_4d(const CUtensorMap* map, int c1, int c2) {
  asm volatile("cp.async.bulk.prefetch.tensor.4d.L2.global.tile [%0, {%1, %2, %3, %1}];"
               ::"l"(map), "r"(0), "r"(c1), "r"(c2) : "memory");
}
__device__ __forceinline__ void tma_load_3d(uint32_t dst, const CUtensorMap* map, uint32_t bar, int c1, int c2) {
  asm volatile("cp.async.bulk.tensor.3d.shared::cluster.global.mbarrier::complete_tx::bytes [%0], [%1, {%3, %4, %5}], [%2];"
               ::"r"(dst), "l"(map), "r"(bar), "r"(0), "r"(c1), "r"(c2) : "memory");
}
__device__ __forceinline__ void tma_load_2d(uint32_t dst, const CUtensorMap* map, uint32_t bar, int c0, int c1) {
  asm volatile("cp.async.bulk.tensor.2d.shared::cluster.global.mbarrier::complete_tx::bytes [%0], [%1, {%3, %4}], [%2];"
               ::"r"(dst), "l"(map), "r"(bar), "r"(c0), "r"(c1) : "memory");
}
__device__ __forceinline__ void tma_store_4d(const CUtensorMap* map, uint32_t src, int c1, int c2, int c3) {
  asm volatile("cp.async.bulk.tensor.4d.global.shared::cta.bulk_group [%0, {%2, %3, %4, %5}], [%1];"
               ::"l"(map), "r"(src), "r"(0), "r"(c1), "r"(c2), "r"(c3) : "memory");
  asm volatile("cp.async.bulk.commit_group;" ::: "memory");
}
__device__ __forceinline__ void tma_store_wait_read() { asm volatile("cp.async.bulk.wait_group.read 0;" ::: "memory"); }
__device__ __forceinline__ void bulk_load(uint32_t dst, const void* src, uint32_t bytes, uint32_t bar) {
  asm volatile("cp.async.bulk.shared::cluster.global.mbarrier::complete_tx::bytes [%0], [%1], %2, [%3];"
               ::"r"(dst), "l"(src), "r"(bytes), "r"(bar) : "memory");
}
__device__ __forceinline__ void cp_async16(uint32_t dst, const void* src) {
  asm volatile("cp.async.cg.shared.global [%0], [%1], 16;" ::"r"(dst), "l"(src) : "memory");
}
__device__ __forceinline__ void prefetch_l2(const void* p, uint32_t bytes) {
  asm volatile("cp.async.bulk.prefetch.L2.global [%0], %1;" ::"l"(p), "r"(bytes) : "memory");
}
__device__ __forceinline__ void stg128(void* p, uint32_t a, uint32_t b, uint32_t c, uint32_t d) {
  asm volatile("st.global.v4.b32 [%0], {%1,%2,%3,%4};" ::"l"(p), "r"(a), "r"(b), "r"(c), "r"(d) : "memory");
}
__device__ __forceinline__ void stsm_x4(uint32_t addr, uint32_t a, uint32_t b, uint32_t c, uint32_t d) {
  asm volatile("stmatrix.sync.aligned.m8n8.x4.shared.b16 [%0], {%1,%2,%3,%4};"
               ::"r"(addr), "r"(a), "r"(b), "r"(c), "r"(d) : "memory");
}
__device__ __forceinline__ void st_async_v4(uint32_t addr, uint32_t mbar, uint32_t a, uint32_t b, uint32_t c, uint32_t d) {
  asm volatile("st.async.weak.shared::cluster.mbarrier::complete_tx::bytes.v4.b32 [%0], {%1,%2,%3,%4}, [%5];"
               ::"r"(addr), "r"(a), "r"(b), "r"(c), "r"(d), "r"(mbar) : "memory");
}
__device__ __forceinline__ uint32_t mapa(uint32_t addr, uint32_t rank) {
  uint32_t r; asm("mapa.shared::cluster.u32 %0, %1, %2;" : "=r"(r) : "r"(addr), "r"(rank)); return r;
}
__device__ __forceinline__ void mbar_init(uint32_t bar, uint32_t count) {
  asm volatile("mbarrier.init.shared::cta.b64 [%0], %1;" ::"r"(bar), "r"(count) : "memory");
}
__device__ __forceinline__ void mbar_arrive_remote(uint32_t bar) {
  asm volatile("mbarrier.arrive.relaxed.cluster.shared::cluster.b64 _, [%0];" ::"r"(bar) : "memory");
}
__device__ __forceinline__ void mbar_arrive_local(uint32_t bar) {
  asm volatile("mbarrier.arrive.shared::cta.b64 _, [%0];" ::"r"(bar) : "memory");
}
__device__ __forceinline__ void mbar_expect_tx(uint32_t bar, uint32_t bytes) {
  asm volatile("mbarrier.arrive.expect_tx.shared::cta.b64 _, [%0], %1;" ::"r"(bar), "r"(bytes) : "memory");
}
__device__ __forceinline__ void mbar_wait(uint32_t bar, uint32_t parity) {
  asm volatile("{\n.reg .pred p, q;\n.reg .u32 c;\nmov.u32 c, 0;\n"
               "WAIT_LOOP:\n"
               "mbarrier.try_wait.parity.shared::cta.b64 p, [%0], %1;\n"
               "@p bra WAIT_DONE;\n"
               "add.u32 c, c, 1;\n"
               "setp.lt.u32 q, c, 0x1000000;\n"
               "@q bra WAIT_LOOP;\n"
               "trap;\n"
               "WAIT_DONE:\n}\n"
               ::"r"(bar), "r"(parity) : "memory");
}
__device__ __forceinline__ void wg_bar(int id) { asm volatile("bar.sync %0, 128;" ::"r"(id) : "memory"); }
__device__ __forceinline__ void fence_async_smem() { asm volatile("fence.proxy.async.shared::cta;" ::: "memory"); }

__device__ __forceinline__ void bias_mask(const uint4 (&b)[4], const uint4 (&mk)[4], uint32_t (&bm)[16]) {
#pragma unroll
  for (int i = 0; i < 4; i++) {
    bm[4 * i] = bf2_fma(mk[i].x, LOG2E_BF16X2, b[i].x);
    bm[4 * i + 1] = bf2_fma(mk[i].y, LOG2E_BF16X2, b[i].y);
    bm[4 * i + 2] = bf2_fma(mk[i].z, LOG2E_BF16X2, b[i].z);
    bm[4 * i + 3] = bf2_fma(mk[i].w, LOG2E_BF16X2, b[i].w);
  }
}
__device__ __forceinline__ void softmax_frag(const float (&s)[32], const uint32_t (&bm)[16],
                                             uint32_t (&pa)[8], uint32_t (&pb)[8]) {
#pragma unroll
  for (int j = 0; j < 8; j++) {
    pa[j] = bf2_add(pack_bf16(s[4 * j], s[4 * j + 1]), bm[j]);
    pb[j] = bf2_add(pack_bf16(s[4 * j + 2], s[4 * j + 3]), bm[8 + j]);
  }
  uint32_t xa = bf2_max(bf2_max(bf2_max(pa[0], pa[1]), bf2_max(pa[2], pa[3])),
                        bf2_max(bf2_max(pa[4], pa[5]), bf2_max(pa[6], pa[7])));
  uint32_t xb = bf2_max(bf2_max(bf2_max(pb[0], pb[1]), bf2_max(pb[2], pb[3])),
                        bf2_max(bf2_max(pb[4], pb[5]), bf2_max(pb[6], pb[7])));
  uint32_t m = bf2_max(__byte_perm(xa, xb, 0x5410), __byte_perm(xa, xb, 0x7632));
  m = bf2_max(m, __shfl_xor_sync(0xffffffffu, m, 1));
  m = bf2_max(m, __shfl_xor_sync(0xffffffffu, m, 2));
  const uint32_t mA = __byte_perm(m, m, 0x1010), mB = __byte_perm(m, m, 0x3232);
#pragma unroll
  for (int j = 0; j < 8; j++) {
    pa[j] = bf2_ex2(bf2_sub(pa[j], mA));
    pb[j] = bf2_ex2(bf2_sub(pb[j], mB));
  }
}
__device__ __forceinline__ void load_bias(const uint4* p, uint4 (&b)[4]) {
#pragma unroll
  for (int i = 0; i < 4; i++) b[i] = ldg_cached(p + 128 * i);
}

constexpr int PREP_PIECES = W_IMG / 16 + 1024;
__global__ void __launch_bounds__(256)
swin_prep_kernel(const __nv_bfloat16* __restrict__ wqkv, const __nv_bfloat16* __restrict__ wo,
                 const __nv_bfloat16* __restrict__ rpb, const int* __restrict__ rp_idx) {
  asm volatile("griddepcontrol.launch_dependents;");
  const int idx = blockIdx.x * 256 + threadIdx.x;
  const int rank = idx / PREP_PIECES;
  int pc = idx - rank * PREP_PIECES;
  if (rank >= 2) return;
  if (pc < (int)(SM_WO / 16)) {
    const int part = pc / 1152, rem = pc - part * 1152;
    const int grp = rem / 384, k = (rem - grp * 384) >> 1, hf = (rem & 1) ^ ((k >> 2) & 1);
    const int sect = (part == 0 || part == 2) ? 192 : (part == 1 || part == 5) ? 384 : 0;
    const int hh = (part == 2 || part == 4 || part == 5) ? 1 : 0;
    uint4 w = __ldg(reinterpret_cast<const uint4*>(wqkv + k * 576 + sect + (2 * rank + hh) * 48 + 16 * grp + 8 * hf));
    if (sect == 0) {
      uint32_t* u = reinterpret_cast<uint32_t*>(&w);
#pragma unroll
      for (int c = 0; c < 4; c++)
        u[c] = pack_bf16(__uint_as_float(u[c] << 16) * QSCALE, __uint_as_float(u[c] & 0xffff0000u) * QSCALE);
    }
    g_wimg[rank][pc] = w;
  } else if (pc < (int)(W_IMG / 16)) {
    const int q0 = pc - SM_WO / 16;
    const int half = q0 / 1152, rem = q0 - half * 1152;
    const int grp = rem / 192, k = (rem - grp * 192) >> 1, hf = (rem & 1) ^ ((k >> 2) & 1);
    int row = 96 * rank + k;
    if (half) {
      const int q = k >> 5, tt = (k >> 3) & 3, r = 4 * q + ((k & 7) >> 1);
      const int hh = r / 6, j = r - hh * 6;
      row = 96 * (rank ^ 1) + hh * 48 + 8 * j + 2 * tt + (k & 1);
    }
    g_wimg[rank][pc] = __ldg(reinterpret_cast<const uint4*>(wo + row * CH + 96 * rank + 16 * grp + 8 * hf));
  } else {
    pc -= W_IMG / 16;
    const int hh = pc >> 9, sel = (pc >> 8) & 1, u = (pc >> 7) & 1, wt = pc & 127;
    const int w4 = wt >> 5, gg = (wt & 31) >> 2, tt = wt & 3;
    const int row = 8 * ((gg >> 1) + 4 * (w4 >> 1)) + 4 * (w4 & 1) + (gg & 1) + 2 * sel;
    const int4* p = reinterpret_cast<const int4*>(rp_idx + row * 64 + 8 * (tt + 4 * u));
    const int4 i0 = __ldg(p), i1 = __ldg(p + 1);
    const int head = 2 * rank + hh;
    auto bv = [&](int i) { return __bfloat162float(rpb[i * 4 + head]) * LOG2E; };
    g_bias[rank][pc] = make_uint4(pack_bf16(bv(i0.x), bv(i0.y)), pack_bf16(bv(i0.z), bv(i0.w)),
                                  pack_bf16(bv(i1.x), bv(i1.y)), pack_bf16(bv(i1.z), bv(i1.w)));
  }
}

__global__ void __cluster_dims__(2, 1, 1) __launch_bounds__(NTHREADS, 1)
swin_window_attn_kernel(const __grid_constant__ CUtensorMap xmap, const __grid_constant__ CUtensorMap ymap,
                        const __nv_bfloat16* __restrict__ mask) {
  extern __shared__ __align__(1024) uint8_t smem[];
  const uint32_t sbase = (uint32_t)__cvta_generic_to_shared(smem);
  const int tid = threadIdx.x;
  const int wg = __shfl_sync(0xffffffffu, tid >> 7, 0);
  const int wtid = tid & 127, lane = tid & 31;
  const int warp = __shfl_sync(0xffffffffu, wtid >> 5, 0);
  const int g = lane >> 2, t = lane & 3;
  uint32_t crank;
  asm("mov.u32 %0, %%cluster_ctarank;" : "=r"(crank));
  const int ncl = gridDim.x >> 1;
  const int cl = blockIdx.x >> 1;

  const int th = (g >> 1) + 4 * (warp >> 1);
  const int tw = 4 * (warp & 1) + (g & 1);
  const int wstride = ncl * NWG;
  int win = wg * ncl + cl;

  const uint32_t bar_rdy = sbase + SM_BAR + wg * 32;
  const uint32_t bar_dat = bar_rdy + 8;
  const uint32_t bar_x0 = sbase + SM_BAR + 96;
  const uint32_t x_quad = sbase + SM_X + warp * X_QUAD;
  auto quad_coords = [&](int w, int& y, int& x) {
    const int wi = w / 48, wj = w - wi * 48;
    y = wi * 8 + 4 + 4 * (warp >> 1);
    x = wj * 8 + 4 + 4 * (warp & 1);
    if (y >= IMG) y -= IMG;
    if (x >= IMG) x -= IMG;
  };
  auto issue_x = [&](int w, int dst_wg) {
    int y, x;
    quad_coords(w, y, x);
    const uint32_t bar = bar_x0 + (dst_wg * 4 + warp) * 8;
    mbar_expect_tx(bar, X_QUAD);
    tma_load_4d(x_quad, &xmap, bar, y, x);
    if ((warp & 1) == crank && w + PF_DIST * ncl < NWIN) {
      quad_coords(w + PF_DIST * ncl, y, x);
      tma_prefetch_4d(&xmap, y, x);
    }
  };

  const uint32_t bar_w = bar_x0 + 96;
  const uint32_t wgbuf = sbase + SM_WG + wg * WG_BYTES;
  const uint64_t d_wqkv = make_desc_sw32(sbase + SM_WQKV, 6144, 256);
  const uint64_t d_wo = make_desc_sw32(sbase + SM_WO, 3072, 256);
  const uint64_t d_k = make_desc(wgbuf, 1024, 128);
  const uint64_t d_v = make_desc(wgbuf, 128, 1024);
  const uint64_t d_ex = make_desc_sw64(wgbuf, 512);
  if (tid == 0) {
#pragma unroll
    for (int i = 0; i < NWG; i++) {
      mbar_init(sbase + SM_BAR + i * 32, 4);
      mbar_init(sbase + SM_BAR + i * 32 + 8, 1);
    }
#pragma unroll
    for (int i = 0; i < 4 * NWG; i++) mbar_init(bar_x0 + i * 8, 1);
    mbar_init(bar_w, 1);
    asm volatile("fence.mbarrier_init.release.cluster;" ::: "memory");
    fence_async_smem();
  }
  *reinterpret_cast<uint2*>(smem + SM_WG + wg * WG_BYTES + OFF_ONES + wtid * 8) = make_uint2(0x3F803F80u, 0x3F803F80u);
  fence_async_smem();
  __syncthreads();
  asm volatile("barrier.cluster.arrive.relaxed.aligned;" ::: "memory");
  if (wg == 0 && lane == 0 && win < NWIN) issue_x(win, 0);
  asm volatile("griddepcontrol.wait;" ::: "memory");
  if (tid == 0) {
    mbar_expect_tx(bar_w, W_IMG);
    const uint8_t* img = reinterpret_cast<const uint8_t*>(g_wimg[crank]);
#pragma unroll
    for (int i = 0; i < 8; i++) bulk_load(sbase + i * (W_IMG / 8), img + i * (W_IMG / 8), W_IMG / 8, bar_w);
  }
  asm volatile("barrier.cluster.wait.acquire.aligned;" ::: "memory");

  const int mi = lane >> 3, r8 = lane & 7;
  const uint32_t t_st = wgbuf + (mi >> 1) * 1024 + (2 * warp + (mi & 1)) * 128 + r8 * 16;
  const uint32_t ex_remote = mapa(wgbuf + (16 * warp + g) * 64 + ((t ^ ((g >> 1) & 3)) << 4), crank ^ 1);
  const uint32_t dat_remote = mapa(bar_dat, crank ^ 1);
  const uint32_t rdy_remote = mapa(bar_rdy, crank ^ 1);
  const uint4* bias_ptr = &g_bias[crank][wtid];
  const uint32_t y_quad = wgbuf + warp * 3072;
  const uint32_t y_st = [&] {
    const int gg = lane & 7, sel = (lane >> 3) & 1, chi = lane >> 4;
    const int r = (2 * sel + (gg & 1)) * 4 + (gg >> 1);
    return y_quad + r * 64 + ((chi ^ ((r >> 1) & 3)) << 4);
  }();

  const uint32_t x_ld = [&] {
    const int gg = lane & 7, sel = (lane >> 3) & 1, khi = lane >> 4;
    const int r = (2 * sel + (gg & 1)) * 4 + (gg >> 1);
    return x_quad + r * 128 + ((khi ^ (r & 7)) << 4);
  }();
  const uint32_t bar_x = bar_x0 + (wg * 4 + warp) * 8;
  const int next_wg = wg == NWG - 1 ? 0 : wg + 1;
  const __nv_bfloat16* mask_thr = mask + (8 * th + tw) * 64 + 8 * t;

  uint4 xa[12];
  auto load_x_frags = [&](bool valid, uint32_t par) {
    if (valid) mbar_wait(bar_x, par);
#pragma unroll
    for (int s = 0; s < 12; s++) ldsm_x4((x_ld ^ ((s & 3) << 5)) + (s >> 2) * 2048, xa[s]);
  };
  load_x_frags(win < NWIN, 0);

  mbar_wait(bar_w, 0);
  uint32_t parity = 0;
  for (; win < NWIN; win += wstride, parity ^= 1) {
    uint4 mk[4];
    {
      float acc[72];
      wg_fence();
#pragma unroll
      for (int s = 0; s < 12; s++) {
        if (s == 0) wgmma_rs_n144_init<1>(acc, xa[s].x, xa[s].y, xa[s].z, xa[s].w, desc_add(d_wqkv, s * 512));
        else        wgmma_rs_n144<1>(acc, xa[s].x, xa[s].y, xa[s].z, xa[s].w, desc_add(d_wqkv, s * 512));
      }
      wg_commit();
      if (lane == 0 && win + ncl < NWIN) issue_x(win + ncl, next_wg);
      if (wtid == 0 && crank == 0 && win + wstride < NWIN) prefetch_l2(mask + (size_t)(win + wstride) * 4096, 8192);
      if (lane == 0) tma_store_wait_read();
      wg_bar(1 + wg);
      const __nv_bfloat16* mp = mask_thr + (size_t)win * 4096;
      mk[0] = ldg_stream(mp);
      mk[1] = ldg_stream(mp + 32);
      mk[2] = ldg_stream(mp + 128);
      mk[3] = ldg_stream(mp + 160);
      wg_wait<0>();
      pin(acc);
#pragma unroll
      for (int j = 0; j < 18; j += 2) {
        const uint32_t off = (j < 6 ? OFF_K0 : j < 12 ? OFF_V0 : OFF_K1) + (j % 6) * 1024;
        stsm_x4(t_st + off, pack_bf16(acc[4 * j], acc[4 * j + 1]), pack_bf16(acc[4 * j + 2], acc[4 * j + 3]),
                pack_bf16(acc[4 * j + 4], acc[4 * j + 5]), pack_bf16(acc[4 * j + 6], acc[4 * j + 7]));
      }
      fence_async_smem();
    }
    float s0[32], s1[32];
    uint32_t v1[12];
    uint32_t bm[16];
    {
      float acc[72];
      wg_fence();
#pragma unroll
      for (int s = 0; s < 12; s++) {
        if (s == 0) wgmma_rs_n144_init<1>(acc, xa[s].x, xa[s].y, xa[s].z, xa[s].w, desc_add(d_wqkv, WQKV_HEAD + s * 512));
        else        wgmma_rs_n144<1>(acc, xa[s].x, xa[s].y, xa[s].z, xa[s].w, desc_add(d_wqkv, WQKV_HEAD + s * 512));
      }
      wg_commit();
      wg_bar(1 + wg);
      uint4 b0[4];
      load_bias(bias_ptr, b0);
      wg_wait<0>();
      pin(acc);
      uint32_t qa[12], qb[12];
#pragma unroll
      for (int j = 0; j < 12; j++) {
        qa[j] = pack_bf16(acc[4 * j], acc[4 * j + 1]);
        qb[j] = pack_bf16(acc[4 * j + 2], acc[4 * j + 3]);
      }
#pragma unroll
      for (int j = 0; j < 12; j++) v1[j] = pack_bf16(acc[48 + 2 * j], acc[48 + 2 * j + 1]);
      wg_fence();
#pragma unroll
      for (int k = 0; k < 3; k++) {
        if (k == 0) wgmma_rs_n64_init<0>(s0, qa[0], qb[0], qa[1], qb[1], desc_add(d_k, OFF_K0));
        else        wgmma_rs_n64<0>(s0, qa[2 * k], qb[2 * k], qa[2 * k + 1], qb[2 * k + 1], desc_add(d_k, OFF_K0 + k * 2048));
      }
      wg_commit();
#pragma unroll
      for (int k = 0; k < 3; k++) {
        if (k == 0) wgmma_rs_n64_init<0>(s1, qa[6], qb[6], qa[7], qb[7], desc_add(d_k, OFF_K1));
        else        wgmma_rs_n64<0>(s1, qa[6 + 2 * k], qb[6 + 2 * k], qa[7 + 2 * k], qb[7 + 2 * k], desc_add(d_k, OFF_K1 + k * 2048));
      }
      wg_commit();
      bias_mask(b0, mk, bm);
      wg_wait<1>();
      pin(s0);
    }
    uint32_t pa[8], pb[8];
    float o0[28];
    wg_bar(1 + wg);
#pragma unroll
    for (int j = 0; j < 3; j++) stsm_x4(t_st + OFF_K0 + j * 2048, v1[4 * j], v1[4 * j + 1], v1[4 * j + 2], v1[4 * j + 3]);
    fence_async_smem();
    uint4 b1[4];
    load_bias(bias_ptr + 512, b1);
    softmax_frag(s0, bm, pa, pb);
    wg_fence();
#pragma unroll
    for (int k = 0; k < 4; k++) {
      if (k == 0) wgmma_rs_n56_init<1>(o0, pa[0], pb[0], pa[1], pb[1], desc_add(d_v, OFF_V0));
      else        wgmma_rs_n56<1>(o0, pa[2 * k], pb[2 * k], pa[2 * k + 1], pb[2 * k + 1], desc_add(d_v, OFF_V0 + k * 256));
    }
    wg_commit();
    bias_mask(b1, mk, bm);
    wg_wait<1>();
    pin(s1);
    uint32_t pc[8], pd[8];
    softmax_frag(s1, bm, pc, pd);
    wg_wait<0>();
    pin(o0);
    if (lane == 0) mbar_arrive_remote(rdy_remote);
    if (wtid == 0) mbar_expect_tx(bar_dat, 64 * 96 * 2);
    wg_bar(1 + wg);
    float o1[28];
    wg_fence();
#pragma unroll
    for (int k = 0; k < 4; k++) {
      if (k == 0) wgmma_rs_n56_init<1>(o1, pc[0], pd[0], pc[1], pd[1], desc_add(d_v, OFF_ONES));
      else        wgmma_rs_n56<1>(o1, pc[2 * k], pd[2 * k], pc[2 * k + 1], pd[2 * k + 1], desc_add(d_v, OFF_ONES + k * 256));
    }
    wg_commit();
    uint32_t oa[12], ob[12], sa[12], sb[12];
    float acc[48];
    {
      const float ra = rcp_approx(o0[24]), rb = rcp_approx(o0[26]);
#pragma unroll
      for (int j = 0; j < 6; j++) {
        const float a0 = o0[4 * j] * ra, a1 = o0[4 * j + 1] * ra, c0 = o0[4 * j + 2] * rb, c1 = o0[4 * j + 3] * rb;
        oa[j] = pack_bf16(a0, a1);
        ob[j] = pack_bf16(c0, c1);
        sa[j] = pack_bf16_v(a0, a1);
        sb[j] = pack_bf16_v(c0, c1);
      }
    }
    wg_fence();
#pragma unroll
    for (int s = 0; s < 3; s++) {
      if (s == 0) wgmma_rs_n96_init<1>(acc, oa[0], ob[0], oa[1], ob[1], d_wo);
      else        wgmma_rs_n96<1>(acc, oa[2 * s], ob[2 * s], oa[2 * s + 1], ob[2 * s + 1], desc_add(d_wo, s * 512));
    }
    wg_commit();
    wg_wait<1>();
    pin(o1);
    {
      const float ra = rcp_approx(o1[0]), rb = rcp_approx(o1[2]);
#pragma unroll
      for (int j = 0; j < 6; j++) {
        const float a0 = o1[4 + 4 * j] * ra, a1 = o1[4 + 4 * j + 1] * ra, c0 = o1[4 + 4 * j + 2] * rb, c1 = o1[4 + 4 * j + 3] * rb;
        oa[6 + j] = pack_bf16(a0, a1);
        ob[6 + j] = pack_bf16(c0, c1);
        sa[6 + j] = pack_bf16_v(a0, a1);
        sb[6 + j] = pack_bf16_v(c0, c1);
      }
    }
    mbar_wait(bar_rdy, parity);
#pragma unroll
    for (int q = 0; q < 3; q++) {
      st_async_v4(ex_remote + q * 4096, dat_remote, sa[4 * q], sa[4 * q + 1], sa[4 * q + 2], sa[4 * q + 3]);
      st_async_v4(ex_remote + q * 4096 + 512, dat_remote, sb[4 * q], sb[4 * q + 1], sb[4 * q + 2], sb[4 * q + 3]);
    }
    wg_fence();
#pragma unroll
    for (int s = 3; s < 6; s++)
      wgmma_rs_n96<1>(acc, oa[2 * s], ob[2 * s], oa[2 * s + 1], ob[2 * s + 1], desc_add(d_wo, s * 512));
    wg_commit();
    mbar_wait(bar_dat, parity);
    fence_async_smem();
    wg_fence();
#pragma unroll
    for (int s = 0; s < 6; s++)
      wgmma_ss_n96<0, 1>(acc, desc_add(d_ex, (s >> 1) * 4096 + (s & 1) * 32), desc_add(d_wo, WO_HALF + s * 512));
    wg_commit();
    load_x_frags(win + wstride < NWIN, parity ^ 1);
    wg_wait<0>();
    pin(acc);
    wg_bar(1 + wg);
#pragma unroll
    for (int j = 0; j < 12; j += 2)
      stsm_x4((y_st ^ ((j & 2) << 4)) + (j >> 2) * 1024, pack_bf16(acc[4 * j], acc[4 * j + 1]), pack_bf16(acc[4 * j + 2], acc[4 * j + 3]),
              pack_bf16(acc[4 * j + 4], acc[4 * j + 5]), pack_bf16(acc[4 * j + 6], acc[4 * j + 7]));
    fence_async_smem();
    __syncwarp();
    if (lane == 0) {
      const int wi = win / 48, wj = win - wi * 48;
      int y = wi * 8 + 4 + 4 * (warp >> 1), x = wj * 8 + 4 + 4 * (warp & 1);
      if (y >= IMG) y -= IMG;
      if (x >= IMG) x -= IMG;
      tma_store_4d(&ymap, y_quad, y, x, 3 * crank);
    }
  }
  if (lane == 0) tma_store_wait_read();
  asm volatile("barrier.cluster.arrive.release.aligned;\nbarrier.cluster.wait.acquire.aligned;" ::: "memory");
}

}

extern "C" void kernel_launch(void* const* d_in, const int* in_sizes, int n_in, void* d_out, int out_size) {
  (void)in_sizes; (void)n_in; (void)out_size;
  typedef CUresult (*EncodeFn)(CUtensorMap*, CUtensorMapDataType, cuuint32_t, void*, const cuuint64_t*, const cuuint64_t*,
                               const cuuint32_t*, const cuuint32_t*, CUtensorMapInterleave, CUtensorMapSwizzle,
                               CUtensorMapL2promotion, CUtensorMapFloatOOBfill);
  static int grid = 0;
  static EncodeFn encode = nullptr;
  if (grid == 0) {
    int dev = 0, sms = 0;
    cudaGetDevice(&dev);
    cudaDeviceGetAttribute(&sms, cudaDevAttrMultiProcessorCount, dev);
    cudaFuncSetAttribute(swin::swin_window_attn_kernel, cudaFuncAttributeMaxDynamicSharedMemorySize, swin::SM_TOTAL);
    void* fn = nullptr;
    cudaDriverEntryPointQueryResult qr;
    cudaGetDriverEntryPoint("cuTensorMapEncodeTiled", &fn, cudaEnableDefault, &qr);
    encode = (EncodeFn)fn;
    grid = sms & ~1;
  }
  CUtensorMap xmap;
  const cuuint64_t dims[4] = {64, 384, 384, 3};
  const cuuint64_t strides[3] = {384ull * 384ull, 384, 128};
  const cuuint32_t box[4] = {64, 4, 4, 3};
  const cuuint32_t estr[4] = {1, 1, 1, 1};
  encode(&xmap, CU_TENSOR_MAP_DATA_TYPE_BFLOAT16, 4, d_in[0], dims, strides, box, estr, CU_TENSOR_MAP_INTERLEAVE_NONE,
         CU_TENSOR_MAP_SWIZZLE_128B, CU_TENSOR_MAP_L2_PROMOTION_L2_128B, CU_TENSOR_MAP_FLOAT_OOB_FILL_NONE);
  CUtensorMap ymap;
  const cuuint64_t ydims[4] = {32, 384, 384, 6};
  const cuuint64_t ystrides[3] = {384ull * 384ull, 384, 64};
  const cuuint32_t ybox[4] = {32, 4, 4, 3};
  encode(&ymap, CU_TENSOR_MAP_DATA_TYPE_BFLOAT16, 4, d_out, ydims, ystrides, ybox, estr, CU_TENSOR_MAP_INTERLEAVE_NONE,
         CU_TENSOR_MAP_SWIZZLE_64B, CU_TENSOR_MAP_L2_PROMOTION_NONE, CU_TENSOR_MAP_FLOAT_OOB_FILL_NONE);
  swin::swin_prep_kernel<<<(2 * swin::PREP_PIECES + 255) / 256, 256, 0, cudaStreamPerThread>>>(
      (const __nv_bfloat16*)d_in[1], (const __nv_bfloat16*)d_in[2], (const __nv_bfloat16*)d_in[3], (const int*)d_in[4]);
  cudaLaunchConfig_t cfg = {};
  cfg.gridDim = dim3(grid);
  cfg.blockDim = dim3(swin::NTHREADS);
  cfg.dynamicSmemBytes = swin::SM_TOTAL;
  cfg.stream = cudaStreamPerThread;
  cudaLaunchAttribute attr[1];
  attr[0].id = cudaLaunchAttributeProgrammaticStreamSerialization;
  attr[0].val.programmaticStreamSerializationAllowed = 1;
  cfg.attrs = attr;
  cfg.numAttrs = 1;
  cudaLaunchKernelEx(&cfg, swin::swin_window_attn_kernel, xmap, ymap, (const __nv_bfloat16*)d_in[5]);
}
```

```cpp
#include <cuda_runtime.h>
#include <cuda_bf16.h>
#include <cuda.h>
#include <stdint.h>

namespace swin {

constexpr int IMG = 384;
constexpr int CH = 192;
constexpr int NWIN = 48 * 48;
constexpr int NWG = 3;
constexpr int NTHREADS = NWG * 128;
#define PF_DIST_ 1
constexpr int PF_DIST = PF_DIST_;

constexpr uint32_t SM_WQKV = 0;
constexpr uint32_t W_PART = 3 * 192 * 32;
constexpr uint32_t WQKV_HEAD = 3 * W_PART;
constexpr uint32_t SM_WO = 2 * WQKV_HEAD;
constexpr uint32_t WO_HALF = 6 * 96 * 32;
constexpr uint32_t SM_X = SM_WO + 2 * WO_HALF;
constexpr uint32_t X_QUAD = 3 * 16 * 128;
constexpr uint32_t SM_WG = SM_X + 4 * X_QUAD;
constexpr uint32_t OFF_K1 = 0;
constexpr uint32_t OFF_V0 = 6144;
constexpr uint32_t OFF_ONES = OFF_V0 + 6144;
constexpr uint32_t OFF_K0 = OFF_ONES + 1024;
constexpr uint32_t WG_BYTES = OFF_K0 + 6144;
constexpr uint32_t SM_BAR = SM_WG + NWG * WG_BYTES;
constexpr uint32_t SM_TOTAL = SM_BAR + 8 * (12 + 12 + 1);
static_assert(SM_X % 1024 == 0, "X stage must be swizzle-atom aligned");
static_assert(SM_TOTAL <= 232448, "shared memory budget");

constexpr float LOG2E = 1.4426950408889634f;
constexpr float QSCALE = 0.14433756729740643f * LOG2E;
constexpr uint32_t LOG2E_BF16X2 = 0x3FB93FB9u;

constexpr uint32_t W_IMG = SM_X;
__device__ __align__(128) uint4 g_wimg[2][W_IMG / 16];
__device__ uint4 g_bias[2][1024];

template <int TB> __device__ __forceinline__ void wgmma_rs_n48_init(float (&d)[24], uint32_t a0, uint32_t a1, uint32_t a2, uint32_t a3, uint64_t desc) {
  asm volatile("wgmma.mma_async.sync.aligned.m64n48k16.f32.bf16.bf16 "
    "{%0, %1, %2, %3, %4, %5, %6, %7, %8, %9, %10, %11, %12, %13, %14, %15, %16, %17, %18, %19, %20, %21, %22, %23}, "
    "{%24, %25, %26, %27}, %28, 0, 1, 1, %29;"
    : "=f"(d[0]), "=f"(d[1]), "=f"(d[2]), "=f"(d[3]), "=f"(d[4]), "=f"(d[5]), "=f"(d[6]), "=f"(d[7]), "=f"(d[8]), "=f"(d[9]), "=f"(d[10]), "=f"(d[11]), "=f"(d[12]), "=f"(d[13]), "=f"(d[14]), "=f"(d[15]), "=f"(d[16]), "=f"(d[17]), "=f"(d[18]), "=f"(d[19]), "=f"(d[20]), "=f"(d[21]), "=f"(d[22]), "=f"(d[23])
    : "r"(a0), "r"(a1), "r"(a2), "r"(a3), "l"(desc), "n"(TB));
}
template <int TB> __device__ __forceinline__ void wgmma_rs_n48(float (&d)[24], uint32_t a0, uint32_t a1, uint32_t a2, uint32_t a3, uint64_t desc) {
  asm volatile("wgmma.mma_async.sync.aligned.m64n48k16.f32.bf16.bf16 "
    "{%0, %1, %2, %3, %4, %5, %6, %7, %8, %9, %10, %11, %12, %13, %14, %15, %16, %17, %18, %19, %20, %21, %22, %23}, "
    "{%24, %25, %26, %27}, %28, 1, 1, 1, %29;"
    : "+f"(d[0]), "+f"(d[1]), "+f"(d[2]), "+f"(d[3]), "+f"(d[4]), "+f"(d[5]), "+f"(d[6]), "+f"(d[7]), "+f"(d[8]), "+f"(d[9]), "+f"(d[10]), "+f"(d[11]), "+f"(d[12]), "+f"(d[13]), "+f"(d[14]), "+f"(d[15]), "+f"(d[16]), "+f"(d[17]), "+f"(d[18]), "+f"(d[19]), "+f"(d[20]), "+f"(d[21]), "+f"(d[22]), "+f"(d[23])
    : "r"(a0), "r"(a1), "r"(a2), "r"(a3), "l"(desc), "n"(TB));
}
template <int TB> __device__ __forceinline__ void wgmma_rs_n56_init(float (&d)[28], uint32_t a0, uint32_t a1, uint32_t a2, uint32_t a3, uint64_t desc) {
  asm volatile("wgmma.mma_async.sync.aligned.m64n56k16.f32.bf16.bf16 "
    "{%0, %1, %2, %3, %4, %5, %6, %7, %8, %9, %10, %11, %12, %13, %14, %15, %16, %17, %18, %19, %20, %21, %22, %23, %24, %25, %26, %27}, "
    "{%28, %29, %30, %31}, %32, 0, 1, 1, %33;"
    : "=f"(d[0]), "=f"(d[1]), "=f"(d[2]), "=f"(d[3]), "=f"(d[4]), "=f"(d[5]), "=f"(d[6]), "=f"(d[7]), "=f"(d[8]), "=f"(d[9]), "=f"(d[10]), "=f"(d[11]), "=f"(d[12]), "=f"(d[13]), "=f"(d[14]), "=f"(d[15]), "=f"(d[16]), "=f"(d[17]), "=f"(d[18]), "=f"(d[19]), "=f"(d[20]), "=f"(d[21]), "=f"(d[22]), "=f"(d[23]), "=f"(d[24]), "=f"(d[25]), "=f"(d[26]), "=f"(d[27])
    : "r"(a0), "r"(a1), "r"(a2), "r"(a3), "l"(desc), "n"(TB));
}
template <int TB> __device__ __forceinline__ void wgmma_rs_n56(float (&d)[28], uint32_t a0, uint32_t a1, uint32_t a2, uint32_t a3, uint64_t desc) {
  asm volatile("wgmma.mma_async.sync.aligned.m64n56k16.f32.bf16.bf16 "
    "{%0, %1, %2, %3, %4, %5, %6, %7, %8, %9, %10, %11, %12, %13, %14, %15, %16, %17, %18, %19, %20, %21, %22, %23, %24, %25, %26, %27}, "
    "{%28, %29, %30, %31}, %32, 1, 1, 1, %33;"
    : "+f"(d[0]), "+f"(d[1]), "+f"(d[2]), "+f"(d[3]), "+f"(d[4]), "+f"(d[5]), "+f"(d[6]), "+f"(d[7]), "+f"(d[8]), "+f"(d[9]), "+f"(d[10]), "+f"(d[11]), "+f"(d[12]), "+f"(d[13]), "+f"(d[14]), "+f"(d[15]), "+f"(d[16]), "+f"(d[17]), "+f"(d[18]), "+f"(d[19]), "+f"(d[20]), "+f"(d[21]), "+f"(d[22]), "+f"(d[23]), "+f"(d[24]), "+f"(d[25]), "+f"(d[26]), "+f"(d[27])
    : "r"(a0), "r"(a1), "r"(a2), "r"(a3), "l"(desc), "n"(TB));
}
template <int TB> __device__ __forceinline__ void wgmma_rs_n64_init(float (&d)[32], uint32_t a0, uint32_t a1, uint32_t a2, uint32_t a3, uint64_t desc) {
  asm volatile("wgmma.mma_async.sync.aligned.m64n64k16.f32.bf16.bf16 "
    "{%0, %1, %2, %3, %4, %5, %6, %7, %8, %9, %10, %11, %12, %13, %14, %15, %16, %17, %18, %19, %20, %21, %22, %23, %24, %25, %26, %27, %28, %29, %30, %31}, "
    "{%32, %33, %34, %35}, %36, 0, 1, 1, %37;"
    : "=f"(d[0]), "=f"(d[1]), "=f"(d[2]), "=f"(d[3]), "=f"(d[4]), "=f"(d[5]), "=f"(d[6]), "=f"(d[7]), "=f"(d[8]), "=f"(d[9]), "=f"(d[10]), "=f"(d[11]), "=f"(d[12]), "=f"(d[13]), "=f"(d[14]), "=f"(d[15]), "=f"(d[16]), "=f"(d[17]), "=f"(d[18]), "=f"(d[19]), "=f"(d[20]), "=f"(d[21]), "=f"(d[22]), "=f"(d[23]), "=f"(d[24]), "=f"(d[25]), "=f"(d[26]), "=f"(d[27]), "=f"(d[28]), "=f"(d[29]), "=f"(d[30]), "=f"(d[31])
    : "r"(a0), "r"(a1), "r"(a2), "r"(a3), "l"(desc), "n"(TB));
}
template <int TB> __device__ __forceinline__ void wgmma_rs_n64(float (&d)[32], uint32_t a0, uint32_t a1, uint32_t a2, uint32_t a3, uint64_t desc) {
  asm volatile("wgmma.mma_async.sync.aligned.m64n64k16.f32.bf16.bf16 "
    "{%0, %1, %2, %3, %4, %5, %6, %7, %8, %9, %10, %11, %12, %13, %14, %15, %16, %17, %18, %19, %20, %21, %22, %23, %24, %25, %26, %27, %28, %29, %30, %31}, "
    "{%32, %33, %34, %35}, %36, 1, 1, 1, %37;"
    : "+f"(d[0]), "+f"(d[1]), "+f"(d[2]), "+f"(d[3]), "+f"(d[4]), "+f"(d[5]), "+f"(d[6]), "+f"(d[7]), "+f"(d[8]), "+f"(d[9]), "+f"(d[10]), "+f"(d[11]), "+f"(d[12]), "+f"(d[13]), "+f"(d[14]), "+f"(d[15]), "+f"(d[16]), "+f"(d[17]), "+f"(d[18]), "+f"(d[19]), "+f"(d[20]), "+f"(d[21]), "+f"(d[22]), "+f"(d[23]), "+f"(d[24]), "+f"(d[25]), "+f"(d[26]), "+f"(d[27]), "+f"(d[28]), "+f"(d[29]), "+f"(d[30]), "+f"(d[31])
    : "r"(a0), "r"(a1), "r"(a2), "r"(a3), "l"(desc), "n"(TB));
}
template <int TB> __device__ __forceinline__ void wgmma_rs_n64_zero(float (&d)[32], uint32_t a0, uint32_t a1, uint32_t a2, uint32_t a3, uint64_t desc) {
  asm volatile("wgmma.mma_async.sync.aligned.m64n64k16.f32.bf16.bf16 "
    "{%0, %1, %2, %3, %4, %5, %6, %7, %8, %9, %10, %11, %12, %13, %14, %15, %16, %17, %18, %19, %20, %21, %22, %23, %24, %25, %26, %27, %28, %29, %30, %31}, "
    "{%32, %33, %34, %35}, %36, 0, 1, 1, %37;"
    : "+f"(d[0]), "+f"(d[1]), "+f"(d[2]), "+f"(d[3]), "+f"(d[4]), "+f"(d[5]), "+f"(d[6]), "+f"(d[7]), "+f"(d[8]), "+f"(d[9]), "+f"(d[10]), "+f"(d[11]), "+f"(d[12]), "+f"(d[13]), "+f"(d[14]), "+f"(d[15]), "+f"(d[16]), "+f"(d[17]), "+f"(d[18]), "+f"(d[19]), "+f"(d[20]), "+f"(d[21]), "+f"(d[22]), "+f"(d[23]), "+f"(d[24]), "+f"(d[25]), "+f"(d[26]), "+f"(d[27]), "+f"(d[28]), "+f"(d[29]), "+f"(d[30]), "+f"(d[31])
    : "r"(a0), "r"(a1), "r"(a2), "r"(a3), "l"(desc), "n"(TB));
}
template <int TB> __device__ __forceinline__ void wgmma_rs_n80_init(float (&d)[40], uint32_t a0, uint32_t a1, uint32_t a2, uint32_t a3, uint64_t desc) {
  asm volatile("wgmma.mma_async.sync.aligned.m64n80k16.f32.bf16.bf16 "
    "{%0, %1, %2, %3, %4, %5, %6, %7, %8, %9, %10, %11, %12, %13, %14, %15, %16, %17, %18, %19, %20, %21, %22, %23, %24, %25, %26, %27, %28, %29, %30, %31, %32, %33, %34, %35, %36, %37, %38, %39}, "
    "{%40, %41, %42, %43}, %44, 0, 1, 1, %45;"
    : "=f"(d[0]), "=f"(d[1]), "=f"(d[2]), "=f"(d[3]), "=f"(d[4]), "=f"(d[5]), "=f"(d[6]), "=f"(d[7]), "=f"(d[8]), "=f"(d[9]), "=f"(d[10]), "=f"(d[11]), "=f"(d[12]), "=f"(d[13]), "=f"(d[14]), "=f"(d[15]), "=f"(d[16]), "=f"(d[17]), "=f"(d[18]), "=f"(d[19]), "=f"(d[20]), "=f"(d[21]), "=f"(d[22]), "=f"(d[23]), "=f"(d[24]), "=f"(d[25]), "=f"(d[26]), "=f"(d[27]), "=f"(d[28]), "=f"(d[29]), "=f"(d[30]), "=f"(d[31]), "=f"(d[32]), "=f"(d[33]), "=f"(d[34]), "=f"(d[35]), "=f"(d[36]), "=f"(d[37]), "=f"(d[38]), "=f"(d[39])
    : "r"(a0), "r"(a1), "r"(a2), "r"(a3), "l"(desc), "n"(TB));
}
template <int TB> __device__ __forceinline__ void wgmma_rs_n80(float (&d)[40], uint32_t a0, uint32_t a1, uint32_t a2, uint32_t a3, uint64_t desc) {
  asm volatile("wgmma.mma_async.sync.aligned.m64n80k16.f32.bf16.bf16 "
    "{%0, %1, %2, %3, %4, %5, %6, %7, %8, %9, %10, %11, %12, %13, %14, %15, %16, %17, %18, %19, %20, %21, %22, %23, %24, %25, %26, %27, %28, %29, %30, %31, %32, %33, %34, %35, %36, %37, %38, %39}, "
    "{%40, %41, %42, %43}, %44, 1, 1, 1, %45;"
    : "+f"(d[0]), "+f"(d[1]), "+f"(d[2]), "+f"(d[3]), "+f"(d[4]), "+f"(d[5]), "+f"(d[6]), "+f"(d[7]), "+f"(d[8]), "+f"(d[9]), "+f"(d[10]), "+f"(d[11]), "+f"(d[12]), "+f"(d[13]), "+f"(d[14]), "+f"(d[15]), "+f"(d[16]), "+f"(d[17]), "+f"(d[18]), "+f"(d[19]), "+f"(d[20]), "+f"(d[21]), "+f"(d[22]), "+f"(d[23]), "+f"(d[24]), "+f"(d[25]), "+f"(d[26]), "+f"(d[27]), "+f"(d[28]), "+f"(d[29]), "+f"(d[30]), "+f"(d[31]), "+f"(d[32]), "+f"(d[33]), "+f"(d[34]), "+f"(d[35]), "+f"(d[36]), "+f"(d[37]), "+f"(d[38]), "+f"(d[39])
    : "r"(a0), "r"(a1), "r"(a2), "r"(a3), "l"(desc), "n"(TB));
}
template <int TB> __device__ __forceinline__ void wgmma_rs_n80_zero(float (&d)[40], uint32_t a0, uint32_t a1, uint32_t a2, uint32_t a3, uint64_t desc) {
  asm volatile("wgmma.mma_async.sync.aligned.m64n80k16.f32.bf16.bf16 "
    "{%0, %1, %2, %3, %4, %5, %6, %7, %8, %9, %10, %11, %12, %13, %14, %15, %16, %17, %18, %19, %20, %21, %22, %23, %24, %25, %26, %27, %28, %29, %30, %31, %32, %33, %34, %35, %36, %37, %38, %39}, "
    "{%40, %41, %42, %43}, %44, 0, 1, 1, %45;"
    : "+f"(d[0]), "+f"(d[1]), "+f"(d[2]), "+f"(d[3]), "+f"(d[4]), "+f"(d[5]), "+f"(d[6]), "+f"(d[7]), "+f"(d[8]), "+f"(d[9]), "+f"(d[10]), "+f"(d[11]), "+f"(d[12]), "+f"(d[13]), "+f"(d[14]), "+f"(d[15]), "+f"(d[16]), "+f"(d[17]), "+f"(d[18]), "+f"(d[19]), "+f"(d[20]), "+f"(d[21]), "+f"(d[22]), "+f"(d[23]), "+f"(d[24]), "+f"(d[25]), "+f"(d[26]), "+f"(d[27]), "+f"(d[28]), "+f"(d[29]), "+f"(d[30]), "+f"(d[31]), "+f"(d[32]), "+f"(d[33]), "+f"(d[34]), "+f"(d[35]), "+f"(d[36]), "+f"(d[37]), "+f"(d[38]), "+f"(d[39])
    : "r"(a0), "r"(a1), "r"(a2), "r"(a3), "l"(desc), "n"(TB));
}
template <int TB> __device__ __forceinline__ void wgmma_rs_n96_init(float (&d)[48], uint32_t a0, uint32_t a1, uint32_t a2, uint32_t a3, uint64_t desc) {
  asm volatile("wgmma.mma_async.sync.aligned.m64n96k16.f32.bf16.bf16 "
    "{%0, %1, %2, %3, %4, %5, %6, %7, %8, %9, %10, %11, %12, %13, %14, %15, %16, %17, %18, %19, %20, %21, %22, %23, %24, %25, %26, %27, %28, %29, %30, %31, %32, %33, %34, %35, %36, %37, %38, %39, %40, %41, %42, %43, %44, %45, %46, %47}, "
    "{%48, %49, %50, %51}, %52, 0, 1, 1, %53;"
    : "=f"(d[0]), "=f"(d[1]), "=f"(d[2]), "=f"(d[3]), "=f"(d[4]), "=f"(d[5]), "=f"(d[6]), "=f"(d[7]), "=f"(d[8]), "=f"(d[9]), "=f"(d[10]), "=f"(d[11]), "=f"(d[12]), "=f"(d[13]), "=f"(d[14]), "=f"(d[15]), "=f"(d[16]), "=f"(d[17]), "=f"(d[18]), "=f"(d[19]), "=f"(d[20]), "=f"(d[21]), "=f"(d[22]), "=f"(d[23]), "=f"(d[24]), "=f"(d[25]), "=f"(d[26]), "=f"(d[27]), "=f"(d[28]), "=f"(d[29]), "=f"(d[30]), "=f"(d[31]), "=f"(d[32]), "=f"(d[33]), "=f"(d[34]), "=f"(d[35]), "=f"(d[36]), "=f"(d[37]), "=f"(d[38]), "=f"(d[39]), "=f"(d[40]), "=f"(d[41]), "=f"(d[42]), "=f"(d[43]), "=f"(d[44]), "=f"(d[45]), "=f"(d[46]), "=f"(d[47])
    : "r"(a0), "r"(a1), "r"(a2), "r"(a3), "l"(desc), "n"(TB));
}
template <int TB> __device__ __forceinline__ void wgmma_rs_n96(float (&d)[48], uint32_t a0, uint32_t a1, uint32_t a2, uint32_t a3, uint64_t desc) {
  asm volatile("wgmma.mma_async.sync.aligned.m64n96k16.f32.bf16.bf16 "
    "{%0, %1, %2, %3, %4, %5, %6, %7, %8, %9, %10, %11, %12, %13, %14, %15, %16, %17, %18, %19, %20, %21, %22, %23, %24, %25, %26, %27, %28, %29, %30, %31, %32, %33, %34, %35, %36, %37, %38, %39, %40, %41, %42, %43, %44, %45, %46, %47}, "
    "{%48, %49, %50, %51}, %52, 1, 1, 1, %53;"
    : "+f"(d[0]), "+f"(d[1]), "+f"(d[2]), "+f"(d[3]), "+f"(d[4]), "+f"(d[5]), "+f"(d[6]), "+f"(d[7]), "+f"(d[8]), "+f"(d[9]), "+f"(d[10]), "+f"(d[11]), "+f"(d[12]), "+f"(d[13]), "+f"(d[14]), "+f"(d[15]), "+f"(d[16]), "+f"(d[17]), "+f"(d[18]), "+f"(d[19]), "+f"(d[20]), "+f"(d[21]), "+f"(d[22]), "+f"(d[23]), "+f"(d[24]), "+f"(d[25]), "+f"(d[26]), "+f"(d[27]), "+f"(d[28]), "+f"(d[29]), "+f"(d[30]), "+f"(d[31]), "+f"(d[32]), "+f"(d[33]), "+f"(d[34]), "+f"(d[35]), "+f"(d[36]), "+f"(d[37]), "+f"(d[38]), "+f"(d[39]), "+f"(d[40]), "+f"(d[41]), "+f"(d[42]), "+f"(d[43]), "+f"(d[44]), "+f"(d[45]), "+f"(d[46]), "+f"(d[47])
    : "r"(a0), "r"(a1), "r"(a2), "r"(a3), "l"(desc), "n"(TB));
}
template <int TB> __device__ __forceinline__ void wgmma_rs_n96_zero(float (&d)[48], uint32_t a0, uint32_t a1, uint32_t a2, uint32_t a3, uint64_t desc) {
  asm volatile("wgmma.mma_async.sync.aligned.m64n96k16.f32.bf16.bf16 "
    "{%0, %1, %2, %3, %4, %5, %6, %7, %8, %9, %10, %11, %12, %13, %14, %15, %16, %17, %18, %19, %20, %21, %22, %23, %24, %25, %26, %27, %28, %29, %30, %31, %32, %33, %34, %35, %36, %37, %38, %39, %40, %41, %42, %43, %44, %45, %46, %47}, "
    "{%48, %49, %50, %51}, %52, 0, 1, 1, %53;"
    : "+f"(d[0]), "+f"(d[1]), "+f"(d[2]), "+f"(d[3]), "+f"(d[4]), "+f"(d[5]), "+f"(d[6]), "+f"(d[7]), "+f"(d[8]), "+f"(d[9]), "+f"(d[10]), "+f"(d[11]), "+f"(d[12]), "+f"(d[13]), "+f"(d[14]), "+f"(d[15]), "+f"(d[16]), "+f"(d[17]), "+f"(d[18]), "+f"(d[19]), "+f"(d[20]), "+f"(d[21]), "+f"(d[22]), "+f"(d[23]), "+f"(d[24]), "+f"(d[25]), "+f"(d[26]), "+f"(d[27]), "+f"(d[28]), "+f"(d[29]), "+f"(d[30]), "+f"(d[31]), "+f"(d[32]), "+f"(d[33]), "+f"(d[34]), "+f"(d[35]), "+f"(d[36]), "+f"(d[37]), "+f"(d[38]), "+f"(d[39]), "+f"(d[40]), "+f"(d[41]), "+f"(d[42]), "+f"(d[43]), "+f"(d[44]), "+f"(d[45]), "+f"(d[46]), "+f"(d[47])
    : "r"(a0), "r"(a1), "r"(a2), "r"(a3), "l"(desc), "n"(TB));
}
template <int TB> __device__ __forceinline__ void wgmma_rs_n144_init(float (&d)[72], uint32_t a0, uint32_t a1, uint32_t a2, uint32_t a3, uint64_t desc) {
  asm volatile("wgmma.mma_async.sync.aligned.m64n144k16.f32.bf16.bf16 "
    "{%0, %1, %2, %3, %4, %5, %6, %7, %8, %9, %10, %11, %12, %13, %14, %15, %16, %17, %18, %19, %20, %21, %22, %23, %24, %25, %26, %27, %28, %29, %30, %31, %32, %33, %34, %35, %36, %37, %38, %39, %40, %41, %42, %43, %44, %45, %46, %47, %48, %49, %50, %51, %52, %53, %54, %55, %56, %57, %58, %59, %60, %61, %62, %63, %64, %65, %66, %67, %68, %69, %70, %71}, "
    "{%72, %73, %74, %75}, %76, 0, 1, 1, %77;"
    : "=f"(d[0]), "=f"(d[1]), "=f"(d[2]), "=f"(d[3]), "=f"(d[4]), "=f"(d[5]), "=f"(d[6]), "=f"(d[7]), "=f"(d[8]), "=f"(d[9]), "=f"(d[10]), "=f"(d[11]), "=f"(d[12]), "=f"(d[13]), "=f"(d[14]), "=f"(d[15]), "=f"(d[16]), "=f"(d[17]), "=f"(d[18]), "=f"(d[19]), "=f"(d[20]), "=f"(d[21]), "=f"(d[22]), "=f"(d[23]), "=f"(d[24]), "=f"(d[25]), "=f"(d[26]), "=f"(d[27]), "=f"(d[28]), "=f"(d[29]), "=f"(d[30]), "=f"(d[31]), "=f"(d[32]), "=f"(d[33]), "=f"(d[34]), "=f"(d[35]), "=f"(d[36]), "=f"(d[37]), "=f"(d[38]), "=f"(d[39]), "=f"(d[40]), "=f"(d[41]), "=f"(d[42]), "=f"(d[43]), "=f"(d[44]), "=f"(d[45]), "=f"(d[46]), "=f"(d[47]), "=f"(d[48]), "=f"(d[49]), "=f"(d[50]), "=f"(d[51]), "=f"(d[52]), "=f"(d[53]), "=f"(d[54]), "=f"(d[55]), "=f"(d[56]), "=f"(d[57]), "=f"(d[58]), "=f"(d[59]), "=f"(d[60]), "=f"(d[61]), "=f"(d[62]), "=f"(d[63]), "=f"(d[64]), "=f"(d[65]), "=f"(d[66]), "=f"(d[67]), "=f"(d[68]), "=f"(d[69]), "=f"(d[70]), "=f"(d[71])
    : "r"(a0), "r"(a1), "r"(a2), "r"(a3), "l"(desc), "n"(TB));
}
template <int TB> __device__ __forceinline__ void wgmma_rs_n144(float (&d)[72], uint32_t a0, uint32_t a1, uint32_t a2, uint32_t a3, uint64_t desc) {
  asm volatile("wgmma.mma_async.sync.aligned.m64n144k16.f32.bf16.bf16 "
    "{%0, %1, %2, %3, %4, %5, %6, %7, %8, %9, %10, %11, %12, %13, %14, %15, %16, %17, %18, %19, %20, %21, %22, %23, %24, %25, %26, %27, %28, %29, %30, %31, %32, %33, %34, %35, %36, %37, %38, %39, %40, %41, %42, %43, %44, %45, %46, %47, %48, %49, %50, %51, %52, %53, %54, %55, %56, %57, %58, %59, %60, %61, %62, %63, %64, %65, %66, %67, %68, %69, %70, %71}, "
    "{%72, %73, %74, %75}, %76, 1, 1, 1, %77;"
    : "+f"(d[0]), "+f"(d[1]), "+f"(d[2]), "+f"(d[3]), "+f"(d[4]), "+f"(d[5]), "+f"(d[6]), "+f"(d[7]), "+f"(d[8]), "+f"(d[9]), "+f"(d[10]), "+f"(d[11]), "+f"(d[12]), "+f"(d[13]), "+f"(d[14]), "+f"(d[15]), "+f"(d[16]), "+f"(d[17]), "+f"(d[18]), "+f"(d[19]), "+f"(d[20]), "+f"(d[21]), "+f"(d[22]), "+f"(d[23]), "+f"(d[24]), "+f"(d[25]), "+f"(d[26]), "+f"(d[27]), "+f"(d[28]), "+f"(d[29]), "+f"(d[30]), "+f"(d[31]), "+f"(d[32]), "+f"(d[33]), "+f"(d[34]), "+f"(d[35]), "+f"(d[36]), "+f"(d[37]), "+f"(d[38]), "+f"(d[39]), "+f"(d[40]), "+f"(d[41]), "+f"(d[42]), "+f"(d[43]), "+f"(d[44]), "+f"(d[45]), "+f"(d[46]), "+f"(d[47]), "+f"(d[48]), "+f"(d[49]), "+f"(d[50]), "+f"(d[51]), "+f"(d[52]), "+f"(d[53]), "+f"(d[54]), "+f"(d[55]), "+f"(d[56]), "+f"(d[57]), "+f"(d[58]), "+f"(d[59]), "+f"(d[60]), "+f"(d[61]), "+f"(d[62]), "+f"(d[63]), "+f"(d[64]), "+f"(d[65]), "+f"(d[66]), "+f"(d[67]), "+f"(d[68]), "+f"(d[69]), "+f"(d[70]), "+f"(d[71])
    : "r"(a0), "r"(a1), "r"(a2), "r"(a3), "l"(desc), "n"(TB));
}
template <int TA, int TB> __device__ __forceinline__ void wgmma_ss_n96_init(float (&d)[48], uint64_t desca, uint64_t descb) {
  asm volatile("wgmma.mma_async.sync.aligned.m64n96k16.f32.bf16.bf16 "
    "{%0, %1, %2, %3, %4, %5, %6, %7, %8, %9, %10, %11, %12, %13, %14, %15, %16, %17, %18, %19, %20, %21, %22, %23, %24, %25, %26, %27, %28, %29, %30, %31, %32, %33, %34, %35, %36, %37, %38, %39, %40, %41, %42, %43, %44, %45, %46, %47}, "
    "%48, %49, 0, 1, 1, %50, %51;"
    : "=f"(d[0]), "=f"(d[1]), "=f"(d[2]), "=f"(d[3]), "=f"(d[4]), "=f"(d[5]), "=f"(d[6]), "=f"(d[7]), "=f"(d[8]), "=f"(d[9]), "=f"(d[10]), "=f"(d[11]), "=f"(d[12]), "=f"(d[13]), "=f"(d[14]), "=f"(d[15]), "=f"(d[16]), "=f"(d[17]), "=f"(d[18]), "=f"(d[19]), "=f"(d[20]), "=f"(d[21]), "=f"(d[22]), "=f"(d[23]), "=f"(d[24]), "=f"(d[25]), "=f"(d[26]), "=f"(d[27]), "=f"(d[28]), "=f"(d[29]), "=f"(d[30]), "=f"(d[31]), "=f"(d[32]), "=f"(d[33]), "=f"(d[34]), "=f"(d[35]), "=f"(d[36]), "=f"(d[37]), "=f"(d[38]), "=f"(d[39]), "=f"(d[40]), "=f"(d[41]), "=f"(d[42]), "=f"(d[43]), "=f"(d[44]), "=f"(d[45]), "=f"(d[46]), "=f"(d[47])
    : "l"(desca), "l"(descb), "n"(TA), "n"(TB));
}
template <int TA, int TB> __device__ __forceinline__ void wgmma_ss_n96(float (&d)[48], uint64_t desca, uint64_t descb) {
  asm volatile("wgmma.mma_async.sync.aligned.m64n96k16.f32.bf16.bf16 "
    "{%0, %1, %2, %3, %4, %5, %6, %7, %8, %9, %10, %11, %12, %13, %14, %15, %16, %17, %18, %19, %20, %21, %22, %23, %24, %25, %26, %27, %28, %29, %30, %31, %32, %33, %34, %35, %36, %37, %38, %39, %40, %41, %42, %43, %44, %45, %46, %47}, "
    "%48, %49, 1, 1, 1, %50, %51;"
    : "+f"(d[0]), "+f"(d[1]), "+f"(d[2]), "+f"(d[3]), "+f"(d[4]), "+f"(d[5]), "+f"(d[6]), "+f"(d[7]), "+f"(d[8]), "+f"(d[9]), "+f"(d[10]), "+f"(d[11]), "+f"(d[12]), "+f"(d[13]), "+f"(d[14]), "+f"(d[15]), "+f"(d[16]), "+f"(d[17]), "+f"(d[18]), "+f"(d[19]), "+f"(d[20]), "+f"(d[21]), "+f"(d[22]), "+f"(d[23]), "+f"(d[24]), "+f"(d[25]), "+f"(d[26]), "+f"(d[27]), "+f"(d[28]), "+f"(d[29]), "+f"(d[30]), "+f"(d[31]), "+f"(d[32]), "+f"(d[33]), "+f"(d[34]), "+f"(d[35]), "+f"(d[36]), "+f"(d[37]), "+f"(d[38]), "+f"(d[39]), "+f"(d[40]), "+f"(d[41]), "+f"(d[42]), "+f"(d[43]), "+f"(d[44]), "+f"(d[45]), "+f"(d[46]), "+f"(d[47])
    : "l"(desca), "l"(descb), "n"(TA), "n"(TB));
}

__device__ __forceinline__ void wg_fence() { asm volatile("wgmma.fence.sync.aligned;" ::: "memory"); }
__device__ __forceinline__ void wg_commit() { asm volatile("wgmma.commit_group.sync.aligned;" ::: "memory"); }
template <int N> __device__ __forceinline__ void wg_wait() {
  asm volatile("wgmma.wait_group.sync.aligned %0;" ::"n"(N) : "memory");
}
template <int N> __device__ __forceinline__ void pin(float (&a)[N]) {
#pragma unroll
  for (int i = 0; i < N; i++) asm volatile("" : "+f"(a[i])::"memory");
}
__device__ __forceinline__ uint64_t make_desc(uint32_t addr, uint32_t lbo, uint32_t sbo) {
  uint32_t lo = ((addr & 0x3FFFF) >> 4) | ((lbo >> 4) << 16);
  uint32_t hi = sbo >> 4;
  return ((uint64_t)hi << 32) | lo;
}
__device__ __forceinline__ uint64_t make_desc_sw32(uint32_t addr, uint32_t lbo, uint32_t sbo) {
  return make_desc(addr, lbo, sbo) | (3ull << 62);
}
__device__ __forceinline__ uint64_t make_desc_sw64(uint32_t addr, uint32_t sbo) {
  return make_desc(addr, 16, sbo) | (2ull << 62);
}
__device__ __forceinline__ uint64_t desc_add(uint64_t d, uint32_t bytes) { return d + (bytes >> 4); }

__device__ __forceinline__ uint32_t pack_bf16(float lo, float hi) {
  uint32_t r;
  asm("cvt.rn.bf16x2.f32 %0, %1, %2;" : "=r"(r) : "f"(hi), "f"(lo));
  return r;
}
__device__ __forceinline__ uint32_t pack_bf16_v(float lo, float hi) {
  uint32_t r;
  asm volatile("cvt.rn.bf16x2.f32 %0, %1, %2;" : "=r"(r) : "f"(hi), "f"(lo));
  return r;
}
__device__ __forceinline__ uint32_t bf2_add(uint32_t a, uint32_t b) {
  uint32_t r; asm("add.rn.bf16x2 %0, %1, %2;" : "=r"(r) : "r"(a), "r"(b)); return r;
}
__device__ __forceinline__ uint32_t bf2_sub(uint32_t a, uint32_t b) {
  uint32_t r; asm("sub.rn.bf16x2 %0, %1, %2;" : "=r"(r) : "r"(a), "r"(b)); return r;
}
__device__ __forceinline__ uint32_t bf2_fma(uint32_t a, uint32_t b, uint32_t c) {
  uint32_t r; asm("fma.rn.bf16x2 %0, %1, %2, %3;" : "=r"(r) : "r"(a), "r"(b), "r"(c)); return r;
}
__device__ __forceinline__ uint32_t bf2_max(uint32_t a, uint32_t b) {
  uint32_t r; asm("max.bf16x2 %0, %1, %2;" : "=r"(r) : "r"(a), "r"(b)); return r;
}
__device__ __forceinline__ uint32_t bf2_ex2(uint32_t a) {
  uint32_t r; asm("ex2.approx.ftz.bf16x2 %0, %1;" : "=r"(r) : "r"(a)); return r;
}
__device__ __forceinline__ float rcp_approx(float a) {
  float r; asm("rcp.approx.ftz.f32 %0, %1;" : "=f"(r) : "f"(a)); return r;
}
__device__ __forceinline__ uint64_t policy_evict_first() {
  uint64_t p;
  asm("createpolicy.fractional.L2::evict_first.b64 %0, 1.0;" : "=l"(p));
  return p;
}
__device__ __forceinline__ uint4 ldg_stream(const void* p) {
  uint4 v;
  asm volatile("ld.global.L1::no_allocate.L2::cache_hint.v4.b32 {%0,%1,%2,%3}, [%4], %5;"
               : "=r"(v.x), "=r"(v.y), "=r"(v.z), "=r"(v.w) : "l"(p), "l"(policy_evict_first()));
  return v;
}
__device__ __forceinline__ uint4 ldg_cached(const void* p) {
  uint4 v;
  asm volatile("ld.global.nc.v4.b32 {%0,%1,%2,%3}, [%4];"
               : "=r"(v.x), "=r"(v.y), "=r"(v.z), "=r"(v.w) : "l"(p));
  return v;
}
__device__ __forceinline__ uint4 lds128(uint32_t addr) {
  uint4 v;
  asm volatile("ld.shared.v4.b32 {%0,%1,%2,%3}, [%4];" : "=r"(v.x), "=r"(v.y), "=r"(v.z), "=r"(v.w) : "r"(addr) : "memory");
  return v;
}
__device__ __forceinline__ void ldsm_x4(uint32_t addr, uint4& v) {
  asm volatile("ldmatrix.sync.aligned.m8n8.x4.shared.b16 {%0,%1,%2,%3}, [%4];"
               : "=r"(v.x), "=r"(v.y), "=r"(v.z), "=r"(v.w) : "r"(addr) : "memory");
}
__device__ __forceinline__ void tma_load_4d(uint32_t dst, const CUtensorMap* map, uint32_t bar, int c1, int c2) {
  asm volatile("cp.async.bulk.tensor.4d.shared::cluster.global.mbarrier::complete_tx::bytes.L2::cache_hint [%0], [%1, {%3, %4, %5, %3}], [%2], %6;"
               ::"r"(dst), "l"(map), "r"(bar), "r"(0), "r"(c1), "r"(c2), "l"(policy_evict_first()) : "memory");
}
__device__ __forceinline__ void tma_prefetch_4d(const CUtensorMap* map, int c1, int c2) {
  asm volatile("cp.async.bulk.prefetch.tensor.4d.L2.global.tile.L2::cache_hint [%0, {%1, %2, %3, %1}], %4;"
               ::"l"(map), "r"(0), "r"(c1), "r"(c2), "l"(policy_evict_first()) : "memory");
}
__device__ __forceinline__ void tma_load_3d(uint32_t dst, const CUtensorMap* map, uint32_t bar, int c1, int c2) {
  asm volatile("cp.async.bulk.tensor.3d.shared::cluster.global.mbarrier::complete_tx::bytes [%0], [%1, {%3, %4, %5}], [%2];"
               ::"r"(dst), "l"(map), "r"(bar), "r"(0), "r"(c1), "r"(c2) : "memory");
}
__device__ __forceinline__ void tma_load_2d(uint32_t dst, const CUtensorMap* map, uint32_t bar, int c0, int c1) {
  asm volatile("cp.async.bulk.tensor.2d.shared::cluster.global.mbarrier::complete_tx::bytes [%0], [%1, {%3, %4}], [%2];"
               ::"r"(dst), "l"(map), "r"(bar), "r"(c0), "r"(c1) : "memory");
}
__device__ __forceinline__ void tma_store_4d(const CUtensorMap* map, uint32_t src, int c1, int c2, int c3) {
  asm volatile("cp.async.bulk.tensor.4d.global.shared::cta.bulk_group [%0, {%2, %3, %4, %5}], [%1];"
               ::"l"(map), "r"(src), "r"(0), "r"(c1), "r"(c2), "r"(c3) : "memory");
  asm volatile("cp.async.bulk.commit_group;" ::: "memory");
}
__device__ __forceinline__ void tma_store_wait_read() { asm volatile("cp.async.bulk.wait_group.read 0;" ::: "memory"); }
__device__ __forceinline__ void bulk_load(uint32_t dst, const void* src, uint32_t bytes, uint32_t bar) {
  asm volatile("cp.async.bulk.shared::cluster.global.mbarrier::complete_tx::bytes [%0], [%1], %2, [%3];"
               ::"r"(dst), "l"(src), "r"(bytes), "r"(bar) : "memory");
}
__device__ __forceinline__ void cp_async16(uint32_t dst, const void* src) {
  asm volatile("cp.async.cg.shared.global [%0], [%1], 16;" ::"r"(dst), "l"(src) : "memory");
}
__device__ __forceinline__ void prefetch_l2(const void* p, uint32_t bytes) {
  asm volatile("cp.async.bulk.prefetch.L2.global.L2::cache_hint [%0], %1, %2;" ::"l"(p), "r"(bytes), "l"(policy_evict_first()) : "memory");
}
__device__ __forceinline__ void stg128(void* p, uint32_t a, uint32_t b, uint32_t c, uint32_t d) {
  asm volatile("st.global.v4.b32 [%0], {%1,%2,%3,%4};" ::"l"(p), "r"(a), "r"(b), "r"(c), "r"(d) : "memory");
}
__device__ __forceinline__ void stsm_x4(uint32_t addr, uint32_t a, uint32_t b, uint32_t c, uint32_t d) {
  asm volatile("stmatrix.sync.aligned.m8n8.x4.shared.b16 [%0], {%1,%2,%3,%4};"
               ::"r"(addr), "r"(a), "r"(b), "r"(c), "r"(d) : "memory");
}
__device__ __forceinline__ void st_async_v4(uint32_t addr, uint32_t mbar, uint32_t a, uint32_t b, uint32_t c, uint32_t d) {
  asm volatile("st.async.weak.shared::cluster.mbarrier::complete_tx::bytes.v4.b32 [%0], {%1,%2,%3,%4}, [%5];"
               ::"r"(addr), "r"(a), "r"(b), "r"(c), "r"(d), "r"(mbar) : "memory");
}
__device__ __forceinline__ void st_async_v2(uint32_t addr, uint32_t mbar, uint32_t a, uint32_t b) {
  asm volatile("st.async.weak.shared::cluster.mbarrier::complete_tx::bytes.v2.b32 [%0], {%1,%2}, [%3];"
               ::"r"(addr), "r"(a), "r"(b), "r"(mbar) : "memory");
}
__device__ __forceinline__ uint32_t mapa(uint32_t addr, uint32_t rank) {
  uint32_t r; asm("mapa.shared::cluster.u32 %0, %1, %2;" : "=r"(r) : "r"(addr), "r"(rank)); return r;
}
__device__ __forceinline__ void mbar_init(uint32_t bar, uint32_t count) {
  asm volatile("mbarrier.init.shared::cta.b64 [%0], %1;" ::"r"(bar), "r"(count) : "memory");
}
__device__ __forceinline__ void mbar_arrive_remote(uint32_t bar) {
  asm volatile("mbarrier.arrive.relaxed.cluster.shared::cluster.b64 _, [%0];" ::"r"(bar) : "memory");
}
__device__ __forceinline__ void mbar_arrive_local(uint32_t bar) {
  asm volatile("mbarrier.arrive.shared::cta.b64 _, [%0];" ::"r"(bar) : "memory");
}
__device__ __forceinline__ void mbar_expect_tx(uint32_t bar, uint32_t bytes) {
  asm volatile("mbarrier.arrive.expect_tx.shared::cta.b64 _, [%0], %1;" ::"r"(bar), "r"(bytes) : "memory");
}
__device__ __forceinline__ void mbar_wait(uint32_t bar, uint32_t parity) {
  asm volatile("{\n.reg .pred p, q;\n.reg .u32 c;\nmov.u32 c, 0;\n"
               "WAIT_LOOP:\n"
               "mbarrier.try_wait.parity.shared::cta.b64 p, [%0], %1;\n"
               "@p bra WAIT_DONE;\n"
               "add.u32 c, c, 1;\n"
               "setp.lt.u32 q, c, 0x1000000;\n"
               "@q bra WAIT_LOOP;\n"
               "trap;\n"
               "WAIT_DONE:\n}\n"
               ::"r"(bar), "r"(parity) : "memory");
}
__device__ __forceinline__ bool elect_one() {
  uint32_t p;
  asm volatile("{\n.reg .pred q;\nelect.sync _|q, 0xffffffff;\nselp.u32 %0, 1, 0, q;\n}\n" : "=r"(p));
  return p != 0;
}
__device__ __forceinline__ void wg_bar(int id) { asm volatile("bar.sync %0, 128;" ::"r"(id) : "memory"); }
__device__ __forceinline__ void fence_async_smem() { asm volatile("fence.proxy.async.shared::cta;" ::: "memory"); }

__device__ __forceinline__ void bias_mask(const uint4 (&b)[4], const uint4 (&mk)[4], uint32_t (&bm)[16]) {
#pragma unroll
  for (int i = 0; i < 4; i++) {
    bm[4 * i] = bf2_fma(mk[i].x, LOG2E_BF16X2, b[i].x);
    bm[4 * i + 1] = bf2_fma(mk[i].y, LOG2E_BF16X2, b[i].y);
    bm[4 * i + 2] = bf2_fma(mk[i].z, LOG2E_BF16X2, b[i].z);
    bm[4 * i + 3] = bf2_fma(mk[i].w, LOG2E_BF16X2, b[i].w);
  }
}
__device__ __forceinline__ void softmax_frag(const float (&s)[32], const uint32_t (&bm)[16],
                                             uint32_t (&pa)[8], uint32_t (&pb)[8]) {
#pragma unroll
  for (int j = 0; j < 8; j++) {
    pa[j] = bf2_add(pack_bf16(s[4 * j], s[4 * j + 1]), bm[j]);
    pb[j] = bf2_add(pack_bf16(s[4 * j + 2], s[4 * j + 3]), bm[8 + j]);
  }
  uint32_t xa = bf2_max(bf2_max(bf2_max(pa[0], pa[1]), bf2_max(pa[2], pa[3])),
                        bf2_max(bf2_max(pa[4], pa[5]), bf2_max(pa[6], pa[7])));
  uint32_t xb = bf2_max(bf2_max(bf2_max(pb[0], pb[1]), bf2_max(pb[2], pb[3])),
                        bf2_max(bf2_max(pb[4], pb[5]), bf2_max(pb[6], pb[7])));
  uint32_t m = bf2_max(__byte_perm(xa, xb, 0x5410), __byte_perm(xa, xb, 0x7632));
  m = bf2_max(m, __shfl_xor_sync(0xffffffffu, m, 1));
  m = bf2_max(m, __shfl_xor_sync(0xffffffffu, m, 2));
  const uint32_t mA = __byte_perm(m, m, 0x1010), mB = __byte_perm(m, m, 0x3232);
#pragma unroll
  for (int j = 0; j < 8; j++) {
    pa[j] = bf2_ex2(bf2_sub(pa[j], mA));
    pb[j] = bf2_ex2(bf2_sub(pb[j], mB));
  }
}
__device__ __forceinline__ void load_bias(const uint4* p, uint4 (&b)[4]) {
#pragma unroll
  for (int i = 0; i < 4; i++) b[i] = ldg_cached(p + 128 * i);
}

constexpr int PREP_PIECES = W_IMG / 16 + 1024;
__global__ void __launch_bounds__(256)
swin_prep_kernel(const __nv_bfloat16* __restrict__ wqkv, const __nv_bfloat16* __restrict__ wo,
                 const __nv_bfloat16* __restrict__ rpb, const int* __restrict__ rp_idx) {
  asm volatile("griddepcontrol.launch_dependents;");
  const int idx = blockIdx.x * 256 + threadIdx.x;
  const int rank = idx / PREP_PIECES;
  int pc = idx - rank * PREP_PIECES;
  if (rank >= 2) return;
  if (pc < (int)(SM_WO / 16)) {
    const int part = pc / 1152, rem = pc - part * 1152;
    const int grp = rem / 384, k = (rem - grp * 384) >> 1, hf = (rem & 1) ^ ((k >> 2) & 1);
    const int sect = (part == 0 || part == 2) ? 192 : (part == 1 || part == 5) ? 384 : 0;
    const int hh = (part == 2 || part == 4 || part == 5) ? 1 : 0;
    uint4 w = __ldg(reinterpret_cast<const uint4*>(wqkv + k * 576 + sect + (2 * rank + hh) * 48 + 16 * grp + 8 * hf));
    if (sect == 0) {
      uint32_t* u = reinterpret_cast<uint32_t*>(&w);
#pragma unroll
      for (int c = 0; c < 4; c++)
        u[c] = pack_bf16(__uint_as_float(u[c] << 16) * QSCALE, __uint_as_float(u[c] & 0xffff0000u) * QSCALE);
    }
    g_wimg[rank][pc] = w;
  } else if (pc < (int)(W_IMG / 16)) {
    const int q0 = pc - SM_WO / 16;
    const int half = q0 / 1152, rem = q0 - half * 1152;
    const int grp = rem / 192, k = (rem - grp * 192) >> 1, hf = (rem & 1) ^ ((k >> 2) & 1);
    int row = 96 * rank + k;
    if (half) {
      const int p = k >> 4, tt = (k >> 2) & 3, i = (k >> 1) & 1;
      row = 96 * (rank ^ 1) + 16 * p + 8 * i + 2 * tt + (k & 1);
    }
    g_wimg[rank][pc] = __ldg(reinterpret_cast<const uint4*>(wo + row * CH + 96 * rank + 16 * grp + 8 * hf));
  } else {
    pc -= W_IMG / 16;
    const int hh = pc >> 9, sel = (pc >> 8) & 1, u = (pc >> 7) & 1, wt = pc & 127;
    const int w4 = wt >> 5, gg = (wt & 31) >> 2, tt = wt & 3;
    const int row = 8 * ((gg >> 1) + 4 * (w4 >> 1)) + 4 * (w4 & 1) + (gg & 1) + 2 * sel;
    const int4* p = reinterpret_cast<const int4*>(rp_idx + row * 64 + 8 * (tt + 4 * u));
    if ((threadIdx.x & 31) < 15) asm volatile("prefetch.global.L1 [%0];" ::"l"(rpb + (threadIdx.x & 31) * 64));
    const int4 i0 = __ldg(p), i1 = __ldg(p + 1);
    const int head = 2 * rank + hh;
    auto bv = [&](int i) { return __bfloat162float(rpb[i * 4 + head]) * LOG2E; };
    g_bias[rank][pc] = make_uint4(pack_bf16(bv(i0.x), bv(i0.y)), pack_bf16(bv(i0.z), bv(i0.w)),
                                  pack_bf16(bv(i1.x), bv(i1.y)), pack_bf16(bv(i1.z), bv(i1.w)));
  }
}

__global__ void __cluster_dims__(2, 1, 1) __launch_bounds__(NTHREADS, 1)
swin_window_attn_kernel(const __grid_constant__ CUtensorMap xmap, const __grid_constant__ CUtensorMap ymap,
                        const __nv_bfloat16* __restrict__ mask) {
  extern __shared__ __align__(1024) uint8_t smem[];
  const uint32_t sbase = (uint32_t)__cvta_generic_to_shared(smem);
  const int tid = threadIdx.x;
  const int wg = __shfl_sync(0xffffffffu, tid >> 7, 0);
  const int wtid = tid & 127, lane = tid & 31;
  const int warp = __shfl_sync(0xffffffffu, wtid >> 5, 0);
  const int g = lane >> 2, t = lane & 3;
  uint32_t crank;
  asm("mov.u32 %0, %%cluster_ctarank;" : "=r"(crank));
  const int ncl = gridDim.x >> 1;
  const int cl = blockIdx.x >> 1;

  const int th = (g >> 1) + 4 * (warp >> 1);
  const int tw = 4 * (warp & 1) + (g & 1);
  const int wstride = ncl * NWG;
  int win = wg * ncl + cl;

  const uint32_t bar_rdy = sbase + SM_BAR + wg * 32;
  const uint32_t bar_dat = bar_rdy + 16;
  const uint32_t bar_x0 = sbase + SM_BAR + 96;
  const uint32_t x_quad = sbase + SM_X + warp * X_QUAD;
  auto quad_coords = [&](int w, int& y, int& x) {
    const int wi = w / 48, wj = w - wi * 48;
    y = wi * 8 + 4 + 4 * (warp >> 1);
    x = wj * 8 + 4 + 4 * (warp & 1);
    if (y >= IMG) y -= IMG;
    if (x >= IMG) x -= IMG;
  };
  auto issue_x = [&](int w, int dst_wg) {
    int y, x;
    quad_coords(w, y, x);
    const uint32_t bar = bar_x0 + (dst_wg * 4 + warp) * 8;
    mbar_expect_tx(bar, X_QUAD);
    tma_load_4d(x_quad, &xmap, bar, y, x);
    if ((warp & 1) == crank && w + PF_DIST * ncl < NWIN) {
      quad_coords(w + PF_DIST * ncl, y, x);
      tma_prefetch_4d(&xmap, y, x);
    }
  };

  const uint32_t bar_w = bar_x0 + 96;
  const uint32_t wgbuf = sbase + SM_WG + wg * WG_BYTES;
  const uint64_t d_wqkv = make_desc_sw32(sbase + SM_WQKV, 6144, 256);
  const uint64_t d_wo = make_desc_sw32(sbase + SM_WO, 3072, 256);
  const uint64_t d_k = make_desc(wgbuf, 1024, 128);
  const uint64_t d_v = make_desc(wgbuf, 128, 1024);
  const uint64_t d_ex = make_desc_sw32(wgbuf, 16, 256);
  if (tid == 0) {
#pragma unroll
    for (int i = 0; i < NWG; i++) {
      mbar_init(sbase + SM_BAR + i * 32, 4);
      mbar_init(sbase + SM_BAR + i * 32 + 8, 4);
      mbar_init(sbase + SM_BAR + i * 32 + 16, 1);
    }
#pragma unroll
    for (int i = 0; i < 4 * NWG; i++) mbar_init(bar_x0 + i * 8, 1);
    mbar_init(bar_w, 1);
    asm volatile("fence.mbarrier_init.release.cluster;" ::: "memory");
    fence_async_smem();
  }
  *reinterpret_cast<uint2*>(smem + SM_WG + wg * WG_BYTES + OFF_ONES + wtid * 8) = make_uint2(0x3F803F80u, 0x3F803F80u);
  fence_async_smem();
  __syncthreads();
  asm volatile("barrier.cluster.arrive.relaxed.aligned;" ::: "memory");
  if (wg == 0 && lane == 0 && win < NWIN) issue_x(win, 0);
  asm volatile("griddepcontrol.wait;" ::: "memory");
  if (tid == 0) {
    mbar_expect_tx(bar_w, W_IMG);
    const uint8_t* img = reinterpret_cast<const uint8_t*>(g_wimg[crank]);
#pragma unroll
    for (int i = 0; i < 8; i++) bulk_load(sbase + i * (W_IMG / 8), img + i * (W_IMG / 8), W_IMG / 8, bar_w);
  }
  asm volatile("barrier.cluster.wait.acquire.aligned;" ::: "memory");

  const int mi = lane >> 3, r8 = lane & 7;
  const uint32_t t_st = wgbuf + (mi >> 1) * 1024 + (2 * warp + (mi & 1)) * 128 + r8 * 16;
  const uint32_t ex_remote = mapa(wgbuf + (16 * warp + g) * 32 + (((t >> 1) ^ (g >> 2)) << 4) + (t & 1) * 8, crank ^ 1);
  const uint32_t dat_remote = mapa(bar_dat, crank ^ 1);
  const uint32_t rdy_remote = mapa(bar_rdy, crank ^ 1);
  const uint4* bias_ptr = &g_bias[crank][wtid];
  const uint32_t y_quad = wgbuf + warp * 3072;
  const uint32_t y_st = [&] {
    const int gg = lane & 7, sel = (lane >> 3) & 1, chi = lane >> 4;
    const int r = (2 * sel + (gg & 1)) * 4 + (gg >> 1);
    return y_quad + r * 64 + ((chi ^ ((r >> 1) & 3)) << 4);
  }();

  const uint32_t x_ld = [&] {
    const int gg = lane & 7, sel = (lane >> 3) & 1, khi = lane >> 4;
    const int r = (2 * sel + (gg & 1)) * 4 + (gg >> 1);
    return x_quad + r * 128 + ((khi ^ (r & 7)) << 4);
  }();
  const uint32_t bar_x = bar_x0 + (wg * 4 + warp) * 8;
  const int next_wg = wg == NWG - 1 ? 0 : wg + 1;
  const uint32_t mask_off = ((8 * th + tw) * 64 + 8 * t) * 2;

  uint4 xa[12];
  auto load_x_frags = [&](bool valid, uint32_t par) {
    if (valid) mbar_wait(bar_x, par);
#pragma unroll
    for (int s = 0; s < 12; s++) ldsm_x4((x_ld ^ ((s & 3) << 5)) + (s >> 2) * 2048, xa[s]);
  };
  load_x_frags(win < NWIN, 0);

  uint4 b0[4];
  load_bias(bias_ptr, b0);
  mbar_wait(bar_w, 0);
  uint32_t parity = 0;
  for (; win < NWIN; win += wstride, parity ^= 1) {
    uint4 mk[4];
    {
      float acc[72];
      wg_fence();
#pragma unroll
      for (int s = 0; s < 12; s++) {
        if (s == 0) wgmma_rs_n144_init<1>(acc, xa[s].x, xa[s].y, xa[s].z, xa[s].w, desc_add(d_wqkv, s * 512));
        else        wgmma_rs_n144<1>(acc, xa[s].x, xa[s].y, xa[s].z, xa[s].w, desc_add(d_wqkv, s * 512));
      }
      wg_commit();
      if (win + ncl < NWIN && elect_one()) issue_x(win + ncl, next_wg);
      if (warp == 0 && crank == 0 && win + wstride < NWIN && elect_one()) prefetch_l2(mask + (size_t)(win + wstride) * 4096, 8192);
      tma_store_wait_read();
      wg_bar(1 + wg);
      const __nv_bfloat16* mp = reinterpret_cast<const __nv_bfloat16*>(reinterpret_cast<const uint8_t*>(mask + (size_t)win * 4096) + mask_off);
      mk[0] = ldg_stream(mp);
      mk[1] = ldg_stream(mp + 32);
      mk[2] = ldg_stream(mp + 128);
      mk[3] = ldg_stream(mp + 160);
      wg_wait<0>();
      pin(acc);
#pragma unroll
      for (int j = 0; j < 18; j += 2) {
        const uint32_t off = (j < 6 ? OFF_K0 : j < 12 ? OFF_V0 : OFF_K1) + (j % 6) * 1024;
        stsm_x4(t_st + off, pack_bf16(acc[4 * j], acc[4 * j + 1]), pack_bf16(acc[4 * j + 2], acc[4 * j + 3]),
                pack_bf16(acc[4 * j + 4], acc[4 * j + 5]), pack_bf16(acc[4 * j + 6], acc[4 * j + 7]));
      }
      fence_async_smem();
    }
    float s0[32], s1[32];
    uint32_t v1[12];
    uint32_t bm[16];
    {
      float acc[72];
      wg_fence();
#pragma unroll
      for (int s = 0; s < 12; s++) {
        if (s == 0) wgmma_rs_n144_init<1>(acc, xa[s].x, xa[s].y, xa[s].z, xa[s].w, desc_add(d_wqkv, WQKV_HEAD + s * 512));
        else        wgmma_rs_n144<1>(acc, xa[s].x, xa[s].y, xa[s].z, xa[s].w, desc_add(d_wqkv, WQKV_HEAD + s * 512));
      }
      wg_commit();
      wg_bar(1 + wg);
      wg_wait<0>();
      pin(acc);
      uint32_t qa[12], qb[12];
#pragma unroll
      for (int j = 0; j < 12; j++) {
        qa[j] = pack_bf16(acc[4 * j], acc[4 * j + 1]);
        qb[j] = pack_bf16(acc[4 * j + 2], acc[4 * j + 3]);
      }
#pragma unroll
      for (int j = 0; j < 12; j++) v1[j] = pack_bf16(acc[48 + 2 * j], acc[48 + 2 * j + 1]);
      wg_fence();
#pragma unroll
      for (int k = 0; k < 3; k++) {
        if (k == 0) wgmma_rs_n64_init<0>(s0, qa[0], qb[0], qa[1], qb[1], desc_add(d_k, OFF_K0));
        else        wgmma_rs_n64<0>(s0, qa[2 * k], qb[2 * k], qa[2 * k + 1], qb[2 * k + 1], desc_add(d_k, OFF_K0 + k * 2048));
      }
      wg_commit();
#pragma unroll
      for (int k = 0; k < 3; k++) {
        if (k == 0) wgmma_rs_n64_init<0>(s1, qa[6], qb[6], qa[7], qb[7], desc_add(d_k, OFF_K1));
        else        wgmma_rs_n64<0>(s1, qa[6 + 2 * k], qb[6 + 2 * k], qa[7 + 2 * k], qb[7 + 2 * k], desc_add(d_k, OFF_K1 + k * 2048));
      }
      wg_commit();
      bias_mask(b0, mk, bm);
      wg_wait<1>();
      pin(s0);
    }
    uint32_t pa[8], pb[8];
    float o0[28];
    wg_bar(1 + wg);
#pragma unroll
    for (int j = 0; j < 3; j++) stsm_x4(t_st + OFF_K0 + j * 2048, v1[4 * j], v1[4 * j + 1], v1[4 * j + 2], v1[4 * j + 3]);
    fence_async_smem();
    uint4 b1[4];
    load_bias(bias_ptr + 512, b1);
    softmax_frag(s0, bm, pa, pb);
    wg_fence();
#pragma unroll
    for (int k = 0; k < 4; k++) {
      if (k == 0) wgmma_rs_n56_init<1>(o0, pa[0], pb[0], pa[1], pb[1], desc_add(d_v, OFF_V0));
      else        wgmma_rs_n56<1>(o0, pa[2 * k], pb[2 * k], pa[2 * k + 1], pb[2 * k + 1], desc_add(d_v, OFF_V0 + k * 256));
    }
    wg_commit();
    bias_mask(b1, mk, bm);
    wg_wait<1>();
    pin(s1);
    if (elect_one()) mbar_arrive_remote(rdy_remote);
    if (warp == 0 && elect_one()) mbar_expect_tx(bar_dat, 64 * 96 * 2);
    uint32_t pc[8], pd[8];
    softmax_frag(s1, bm, pc, pd);
    wg_wait<0>();
    pin(o0);
    if (elect_one()) mbar_arrive_remote(rdy_remote + 8);
    wg_bar(1 + wg);
    float o1[28];
    wg_fence();
#pragma unroll
    for (int k = 0; k < 4; k++) {
      if (k == 0) wgmma_rs_n56_init<1>(o1, pc[0], pd[0], pc[1], pd[1], desc_add(d_v, OFF_ONES));
      else        wgmma_rs_n56<1>(o1, pc[2 * k], pd[2 * k], pc[2 * k + 1], pd[2 * k + 1], desc_add(d_v, OFF_ONES + k * 256));
    }
    wg_commit();
    uint32_t oa[12], ob[12], sa[12], sb[12];
    float acc[48];
    {
      const float ra = rcp_approx(o0[24]), rb = rcp_approx(o0[26]);
#pragma unroll
      for (int j = 0; j < 6; j++) {
        const float a0 = o0[4 * j] * ra, a1 = o0[4 * j + 1] * ra, c0 = o0[4 * j + 2] * rb, c1 = o0[4 * j + 3] * rb;
        oa[j] = pack_bf16(a0, a1);
        ob[j] = pack_bf16(c0, c1);
        sa[j] = pack_bf16_v(a0, a1);
        sb[j] = pack_bf16_v(c0, c1);
      }
    }
    mbar_wait(bar_rdy, parity);
#pragma unroll
    for (int p = 0; p < 3; p++) {
      st_async_v2(ex_remote + OFF_K1 + p * 2048, dat_remote, sa[2 * p], sa[2 * p + 1]);
      st_async_v2(ex_remote + OFF_K1 + p * 2048 + 256, dat_remote, sb[2 * p], sb[2 * p + 1]);
    }
    wg_fence();
#pragma unroll
    for (int s = 0; s < 3; s++) {
      if (s == 0) wgmma_rs_n96_init<1>(acc, oa[0], ob[0], oa[1], ob[1], d_wo);
      else        wgmma_rs_n96<1>(acc, oa[2 * s], ob[2 * s], oa[2 * s + 1], ob[2 * s + 1], desc_add(d_wo, s * 512));
    }
    wg_commit();
    wg_wait<1>();
    pin(o1);
    {
      const float ra = rcp_approx(o1[0]), rb = rcp_approx(o1[2]);
#pragma unroll
      for (int j = 0; j < 6; j++) {
        const float a0 = o1[4 + 4 * j] * ra, a1 = o1[4 + 4 * j + 1] * ra, c0 = o1[4 + 4 * j + 2] * rb, c1 = o1[4 + 4 * j + 3] * rb;
        oa[6 + j] = pack_bf16(a0, a1);
        ob[6 + j] = pack_bf16(c0, c1);
        sa[6 + j] = pack_bf16_v(a0, a1);
        sb[6 + j] = pack_bf16_v(c0, c1);
      }
    }
    mbar_wait(bar_rdy + 8, parity);
#pragma unroll
    for (int p = 0; p < 3; p++) {
      st_async_v2(ex_remote + OFF_V0 + p * 2048, dat_remote, sa[6 + 2 * p], sa[6 + 2 * p + 1]);
      st_async_v2(ex_remote + OFF_V0 + p * 2048 + 256, dat_remote, sb[6 + 2 * p], sb[6 + 2 * p + 1]);
    }
    wg_fence();
#pragma unroll
    for (int s = 3; s < 6; s++)
      wgmma_rs_n96<1>(acc, oa[2 * s], ob[2 * s], oa[2 * s + 1], ob[2 * s + 1], desc_add(d_wo, s * 512));
    wg_commit();
    mbar_wait(bar_dat, parity);
    fence_async_smem();
    wg_fence();
#pragma unroll
    for (int s = 0; s < 6; s++)
      wgmma_ss_n96<0, 1>(acc, desc_add(d_ex, s * 2048), desc_add(d_wo, WO_HALF + s * 512));
    wg_commit();
    load_x_frags(win + wstride < NWIN, parity ^ 1);
    wg_wait<0>();
    pin(acc);
    wg_bar(1 + wg);
#pragma unroll
    for (int j = 0; j < 12; j += 2)
      stsm_x4((y_st ^ ((j & 2) << 4)) + (j >> 2) * 1024, pack_bf16(acc[4 * j], acc[4 * j + 1]), pack_bf16(acc[4 * j + 2], acc[4 * j + 3]),
              pack_bf16(acc[4 * j + 4], acc[4 * j + 5]), pack_bf16(acc[4 * j + 6], acc[4 * j + 7]));
    fence_async_smem();
    __syncwarp();
    if (elect_one()) {
      const int wi = win / 48, wj = win - wi * 48;
      int y = wi * 8 + 4 + 4 * (warp >> 1), x = wj * 8 + 4 + 4 * (warp & 1);
      if (y >= IMG) y -= IMG;
      if (x >= IMG) x -= IMG;
      tma_store_4d(&ymap, y_quad, y, x, 3 * crank);
    }
  }
  tma_store_wait_read();
  asm volatile("barrier.cluster.arrive.release.aligned;\nbarrier.cluster.wait.acquire.aligned;" ::: "memory");
}

}

extern "C" void kernel_launch(void* const* d_in, const int* in_sizes, int n_in, void* d_out, int out_size) {
  (void)in_sizes; (void)n_in; (void)out_size;
  typedef CUresult (*EncodeFn)(CUtensorMap*, CUtensorMapDataType, cuuint32_t, void*, const cuuint64_t*, const cuuint64_t*,
                               const cuuint32_t*, const cuuint32_t*, CUtensorMapInterleave, CUtensorMapSwizzle,
                               CUtensorMapL2promotion, CUtensorMapFloatOOBfill);
  static int grid = 0;
  static EncodeFn encode = nullptr;
  if (grid == 0) {
    int dev = 0, sms = 0;
    cudaGetDevice(&dev);
    cudaDeviceGetAttribute(&sms, cudaDevAttrMultiProcessorCount, dev);
    cudaFuncSetAttribute(swin::swin_window_attn_kernel, cudaFuncAttributeMaxDynamicSharedMemorySize, swin::SM_TOTAL);
    void* fn = nullptr;
    cudaDriverEntryPointQueryResult qr;
    cudaGetDriverEntryPoint("cuTensorMapEncodeTiled", &fn, cudaEnableDefault, &qr);
    encode = (EncodeFn)fn;
    grid = sms & ~1;
  }
  CUtensorMap xmap;
  const cuuint64_t dims[4] = {64, 384, 384, 3};
  const cuuint64_t strides[3] = {384ull * 384ull, 384, 128};
  const cuuint32_t box[4] = {64, 4, 4, 3};
  const cuuint32_t estr[4] = {1, 1, 1, 1};
  encode(&xmap, CU_TENSOR_MAP_DATA_TYPE_BFLOAT16, 4, d_in[0], dims, strides, box, estr, CU_TENSOR_MAP_INTERLEAVE_NONE,
         CU_TENSOR_MAP_SWIZZLE_128B, CU_TENSOR_MAP_L2_PROMOTION_NONE, CU_TENSOR_MAP_FLOAT_OOB_FILL_NONE);
  CUtensorMap ymap;
  const cuuint64_t ydims[4] = {32, 384, 384, 6};
  const cuuint64_t ystrides[3] = {384ull * 384ull, 384, 64};
  const cuuint32_t ybox[4] = {32, 4, 4, 3};
  encode(&ymap, CU_TENSOR_MAP_DATA_TYPE_BFLOAT16, 4, d_out, ydims, ystrides, ybox, estr, CU_TENSOR_MAP_INTERLEAVE_NONE,
         CU_TENSOR_MAP_SWIZZLE_64B, CU_TENSOR_MAP_L2_PROMOTION_NONE, CU_TENSOR_MAP_FLOAT_OOB_FILL_NONE);
  swin::swin_prep_kernel<<<(2 * swin::PREP_PIECES + 255) / 256, 256, 0, cudaStreamPerThread>>>(
      (const __nv_bfloat16*)d_in[1], (const __nv_bfloat16*)d_in[2], (const __nv_bfloat16*)d_in[3], (const int*)d_in[4]);
  cudaLaunchConfig_t cfg = {};
  cfg.gridDim = dim3(grid);
  cfg.blockDim = dim3(swin::NTHREADS);
  cfg.dynamicSmemBytes = swin::SM_TOTAL;
  cfg.stream = cudaStreamPerThread;
  cudaLaunchAttribute attr[1];
  attr[0].id = cudaLaunchAttributeProgrammaticStreamSerialization;
  attr[0].val.programmaticStreamSerializationAllowed = 1;
  cfg.attrs = attr;
  cfg.numAttrs = 1;
  cudaLaunchKernelEx(&cfg, swin::swin_window_attn_kernel, xmap, ymap, (const __nv_bfloat16*)d_in[5]);
}
```

```cpp
#include <cuda_runtime.h>
#include <cuda_bf16.h>
#include <cuda.h>
#include <stdint.h>

namespace swin {

constexpr int IMG = 384;
constexpr int CH = 192;
constexpr int NWIN = 48 * 48;
constexpr int NWG = 3;
constexpr int NTHREADS = NWG * 128;
constexpr int PF_DIST = 1;

constexpr uint32_t SM_WQKV = 0;
constexpr uint32_t W_PART = 3 * 192 * 32;
constexpr uint32_t WQKV_HEAD = 3 * W_PART;
constexpr uint32_t SM_WO = 2 * WQKV_HEAD;
constexpr uint32_t WO_HALF = 6 * 96 * 32;
constexpr uint32_t SM_X = SM_WO + 2 * WO_HALF;
constexpr uint32_t X_QUAD = 3 * 16 * 128;
constexpr uint32_t SM_WG = SM_X + 4 * X_QUAD;
constexpr uint32_t OFF_K1 = 0;
constexpr uint32_t OFF_V0 = 6144;
constexpr uint32_t OFF_ONES = OFF_V0 + 6144;
constexpr uint32_t OFF_K0 = OFF_ONES + 1024;
constexpr uint32_t WG_BYTES = OFF_K0 + 6144;
constexpr uint32_t SM_BAR = SM_WG + NWG * WG_BYTES;
constexpr uint32_t SM_TOTAL = SM_BAR + 8 * (12 + 12 + 1);
static_assert(SM_X % 1024 == 0, "X stage must be swizzle-atom aligned");
static_assert(SM_TOTAL <= 232448, "shared memory budget");

constexpr float LOG2E = 1.4426950408889634f;
constexpr float QSCALE = 0.14433756729740643f * LOG2E;
constexpr uint32_t LOG2E_BF16X2 = 0x3FB93FB9u;

constexpr uint32_t W_IMG = SM_X;
__device__ __align__(128) uint4 g_wimg[2][W_IMG / 16];
__device__ uint4 g_bias[2][1024];

template <int TB> __device__ __forceinline__ void wgmma_rs_n56_init(float (&d)[28], uint32_t a0, uint32_t a1, uint32_t a2, uint32_t a3, uint64_t desc) {
  asm volatile("wgmma.mma_async.sync.aligned.m64n56k16.f32.bf16.bf16 "
    "{%0, %1, %2, %3, %4, %5, %6, %7, %8, %9, %10, %11, %12, %13, %14, %15, %16, %17, %18, %19, %20, %21, %22, %23, %24, %25, %26, %27}, "
    "{%28, %29, %30, %31}, %32, 0, 1, 1, %33;"
    : "=f"(d[0]), "=f"(d[1]), "=f"(d[2]), "=f"(d[3]), "=f"(d[4]), "=f"(d[5]), "=f"(d[6]), "=f"(d[7]), "=f"(d[8]), "=f"(d[9]), "=f"(d[10]), "=f"(d[11]), "=f"(d[12]), "=f"(d[13]), "=f"(d[14]), "=f"(d[15]), "=f"(d[16]), "=f"(d[17]), "=f"(d[18]), "=f"(d[19]), "=f"(d[20]), "=f"(d[21]), "=f"(d[22]), "=f"(d[23]), "=f"(d[24]), "=f"(d[25]), "=f"(d[26]), "=f"(d[27])
    : "r"(a0), "r"(a1), "r"(a2), "r"(a3), "l"(desc), "n"(TB));
}
template <int TB> __device__ __forceinline__ void wgmma_rs_n56(float (&d)[28], uint32_t a0, uint32_t a1, uint32_t a2, uint32_t a3, uint64_t desc) {
  asm volatile("wgmma.mma_async.sync.aligned.m64n56k16.f32.bf16.bf16 "
    "{%0, %1, %2, %3, %4, %5, %6, %7, %8, %9, %10, %11, %12, %13, %14, %15, %16, %17, %18, %19, %20, %21, %22, %23, %24, %25, %26, %27}, "
    "{%28, %29, %30, %31}, %32, 1, 1, 1, %33;"
    : "+f"(d[0]), "+f"(d[1]), "+f"(d[2]), "+f"(d[3]), "+f"(d[4]), "+f"(d[5]), "+f"(d[6]), "+f"(d[7]), "+f"(d[8]), "+f"(d[9]), "+f"(d[10]), "+f"(d[11]), "+f"(d[12]), "+f"(d[13]), "+f"(d[14]), "+f"(d[15]), "+f"(d[16]), "+f"(d[17]), "+f"(d[18]), "+f"(d[19]), "+f"(d[20]), "+f"(d[21]), "+f"(d[22]), "+f"(d[23]), "+f"(d[24]), "+f"(d[25]), "+f"(d[26]), "+f"(d[27])
    : "r"(a0), "r"(a1), "r"(a2), "r"(a3), "l"(desc), "n"(TB));
}
template <int TB> __device__ __forceinline__ void wgmma_rs_n64_init(float (&d)[32], uint32_t a0, uint32_t a1, uint32_t a2, uint32_t a3, uint64_t desc) {
  asm volatile("wgmma.mma_async.sync.aligned.m64n64k16.f32.bf16.bf16 "
    "{%0, %1, %2, %3, %4, %5, %6, %7, %8, %9, %10, %11, %12, %13, %14, %15, %16, %17, %18, %19, %20, %21, %22, %23, %24, %25, %26, %27, %28, %29, %30, %31}, "
    "{%32, %33, %34, %35}, %36, 0, 1, 1, %37;"
    : "=f"(d[0]), "=f"(d[1]), "=f"(d[2]), "=f"(d[3]), "=f"(d[4]), "=f"(d[5]), "=f"(d[6]), "=f"(d[7]), "=f"(d[8]), "=f"(d[9]), "=f"(d[10]), "=f"(d[11]), "=f"(d[12]), "=f"(d[13]), "=f"(d[14]), "=f"(d[15]), "=f"(d[16]), "=f"(d[17]), "=f"(d[18]), "=f"(d[19]), "=f"(d[20]), "=f"(d[21]), "=f"(d[22]), "=f"(d[23]), "=f"(d[24]), "=f"(d[25]), "=f"(d[26]), "=f"(d[27]), "=f"(d[28]), "=f"(d[29]), "=f"(d[30]), "=f"(d[31])
    : "r"(a0), "r"(a1), "r"(a2), "r"(a3), "l"(desc), "n"(TB));
}
template <int TB> __device__ __forceinline__ void wgmma_rs_n64(float (&d)[32], uint32_t a0, uint32_t a1, uint32_t a2, uint32_t a3, uint64_t desc) {
  asm volatile("wgmma.mma_async.sync.aligned.m64n64k16.f32.bf16.bf16 "
    "{%0, %1, %2, %3, %4, %5, %6, %7, %8, %9, %10, %11, %12, %13, %14, %15, %16, %17, %18, %19, %20, %21, %22, %23, %24, %25, %26, %27, %28, %29, %30, %31}, "
    "{%32, %33, %34, %35}, %36, 1, 1, 1, %37;"
    : "+f"(d[0]), "+f"(d[1]), "+f"(d[2]), "+f"(d[3]), "+f"(d[4]), "+f"(d[5]), "+f"(d[6]), "+f"(d[7]), "+f"(d[8]), "+f"(d[9]), "+f"(d[10]), "+f"(d[11]), "+f"(d[12]), "+f"(d[13]), "+f"(d[14]), "+f"(d[15]), "+f"(d[16]), "+f"(d[17]), "+f"(d[18]), "+f"(d[19]), "+f"(d[20]), "+f"(d[21]), "+f"(d[22]), "+f"(d[23]), "+f"(d[24]), "+f"(d[25]), "+f"(d[26]), "+f"(d[27]), "+f"(d[28]), "+f"(d[29]), "+f"(d[30]), "+f"(d[31])
    : "r"(a0), "r"(a1), "r"(a2), "r"(a3), "l"(desc), "n"(TB));
}
template <int TB> __device__ __forceinline__ void wgmma_rs_n96_init(float (&d)[48], uint32_t a0, uint32_t a1, uint32_t a2, uint32_t a3, uint64_t desc) {
  asm volatile("wgmma.mma_async.sync.aligned.m64n96k16.f32.bf16.bf16 "
    "{%0, %1, %2, %3, %4, %5, %6, %7, %8, %9, %10, %11, %12, %13, %14, %15, %16, %17, %18, %19, %20, %21, %22, %23, %24, %25, %26, %27, %28, %29, %30, %31, %32, %33, %34, %35, %36, %37, %38, %39, %40, %41, %42, %43, %44, %45, %46, %47}, "
    "{%48, %49, %50, %51}, %52, 0, 1, 1, %53;"
    : "=f"(d[0]), "=f"(d[1]), "=f"(d[2]), "=f"(d[3]), "=f"(d[4]), "=f"(d[5]), "=f"(d[6]), "=f"(d[7]), "=f"(d[8]), "=f"(d[9]), "=f"(d[10]), "=f"(d[11]), "=f"(d[12]), "=f"(d[13]), "=f"(d[14]), "=f"(d[15]), "=f"(d[16]), "=f"(d[17]), "=f"(d[18]), "=f"(d[19]), "=f"(d[20]), "=f"(d[21]), "=f"(d[22]), "=f"(d[23]), "=f"(d[24]), "=f"(d[25]), "=f"(d[26]), "=f"(d[27]), "=f"(d[28]), "=f"(d[29]), "=f"(d[30]), "=f"(d[31]), "=f"(d[32]), "=f"(d[33]), "=f"(d[34]), "=f"(d[35]), "=f"(d[36]), "=f"(d[37]), "=f"(d[38]), "=f"(d[39]), "=f"(d[40]), "=f"(d[41]), "=f"(d[42]), "=f"(d[43]), "=f"(d[44]), "=f"(d[45]), "=f"(d[46]), "=f"(d[47])
    : "r"(a0), "r"(a1), "r"(a2), "r"(a3), "l"(desc), "n"(TB));
}
template <int TB> __device__ __forceinline__ void wgmma_rs_n96(float (&d)[48], uint32_t a0, uint32_t a1, uint32_t a2, uint32_t a3, uint64_t desc) {
  asm volatile("wgmma.mma_async.sync.aligned.m64n96k16.f32.bf16.bf16 "
    "{%0, %1, %2, %3, %4, %5, %6, %7, %8, %9, %10, %11, %12, %13, %14, %15, %16, %17, %18, %19, %20, %21, %22, %23, %24, %25, %26, %27, %28, %29, %30, %31, %32, %33, %34, %35, %36, %37, %38, %39, %40, %41, %42, %43, %44, %45, %46, %47}, "
    "{%48, %49, %50, %51}, %52, 1, 1, 1, %53;"
    : "+f"(d[0]), "+f"(d[1]), "+f"(d[2]), "+f"(d[3]), "+f"(d[4]), "+f"(d[5]), "+f"(d[6]), "+f"(d[7]), "+f"(d[8]), "+f"(d[9]), "+f"(d[10]), "+f"(d[11]), "+f"(d[12]), "+f"(d[13]), "+f"(d[14]), "+f"(d[15]), "+f"(d[16]), "+f"(d[17]), "+f"(d[18]), "+f"(d[19]), "+f"(d[20]), "+f"(d[21]), "+f"(d[22]), "+f"(d[23]), "+f"(d[24]), "+f"(d[25]), "+f"(d[26]), "+f"(d[27]), "+f"(d[28]), "+f"(d[29]), "+f"(d[30]), "+f"(d[31]), "+f"(d[32]), "+f"(d[33]), "+f"(d[34]), "+f"(d[35]), "+f"(d[36]), "+f"(d[37]), "+f"(d[38]), "+f"(d[39]), "+f"(d[40]), "+f"(d[41]), "+f"(d[42]), "+f"(d[43]), "+f"(d[44]), "+f"(d[45]), "+f"(d[46]), "+f"(d[47])
    : "r"(a0), "r"(a1), "r"(a2), "r"(a3), "l"(desc), "n"(TB));
}
template <int TB> __device__ __forceinline__ void wgmma_rs_n144_init(float (&d)[72], uint32_t a0, uint32_t a1, uint32_t a2, uint32_t a3, uint64_t desc) {
  asm volatile("wgmma.mma_async.sync.aligned.m64n144k16.f32.bf16.bf16 "
    "{%0, %1, %2, %3, %4, %5, %6, %7, %8, %9, %10, %11, %12, %13, %14, %15, %16, %17, %18, %19, %20, %21, %22, %23, %24, %25, %26, %27, %28, %29, %30, %31, %32, %33, %34, %35, %36, %37, %38, %39, %40, %41, %42, %43, %44, %45, %46, %47, %48, %49, %50, %51, %52, %53, %54, %55, %56, %57, %58, %59, %60, %61, %62, %63, %64, %65, %66, %67, %68, %69, %70, %71}, "
    "{%72, %73, %74, %75}, %76, 0, 1, 1, %77;"
    : "=f"(d[0]), "=f"(d[1]), "=f"(d[2]), "=f"(d[3]), "=f"(d[4]), "=f"(d[5]), "=f"(d[6]), "=f"(d[7]), "=f"(d[8]), "=f"(d[9]), "=f"(d[10]), "=f"(d[11]), "=f"(d[12]), "=f"(d[13]), "=f"(d[14]), "=f"(d[15]), "=f"(d[16]), "=f"(d[17]), "=f"(d[18]), "=f"(d[19]), "=f"(d[20]), "=f"(d[21]), "=f"(d[22]), "=f"(d[23]), "=f"(d[24]), "=f"(d[25]), "=f"(d[26]), "=f"(d[27]), "=f"(d[28]), "=f"(d[29]), "=f"(d[30]), "=f"(d[31]), "=f"(d[32]), "=f"(d[33]), "=f"(d[34]), "=f"(d[35]), "=f"(d[36]), "=f"(d[37]), "=f"(d[38]), "=f"(d[39]), "=f"(d[40]), "=f"(d[41]), "=f"(d[42]), "=f"(d[43]), "=f"(d[44]), "=f"(d[45]), "=f"(d[46]), "=f"(d[47]), "=f"(d[48]), "=f"(d[49]), "=f"(d[50]), "=f"(d[51]), "=f"(d[52]), "=f"(d[53]), "=f"(d[54]), "=f"(d[55]), "=f"(d[56]), "=f"(d[57]), "=f"(d[58]), "=f"(d[59]), "=f"(d[60]), "=f"(d[61]), "=f"(d[62]), "=f"(d[63]), "=f"(d[64]), "=f"(d[65]), "=f"(d[66]), "=f"(d[67]), "=f"(d[68]), "=f"(d[69]), "=f"(d[70]), "=f"(d[71])
    : "r"(a0), "r"(a1), "r"(a2), "r"(a3), "l"(desc), "n"(TB));
}
template <int TB> __device__ __forceinline__ void wgmma_rs_n144(float (&d)[72], uint32_t a0, uint32_t a1, uint32_t a2, uint32_t a3, uint64_t desc) {
  asm volatile("wgmma.mma_async.sync.aligned.m64n144k16.f32.bf16.bf16 "
    "{%0, %1, %2, %3, %4, %5, %6, %7, %8, %9, %10, %11, %12, %13, %14, %15, %16, %17, %18, %19, %20, %21, %22, %23, %24, %25, %26, %27, %28, %29, %30, %31, %32, %33, %34, %35, %36, %37, %38, %39, %40, %41, %42, %43, %44, %45, %46, %47, %48, %49, %50, %51, %52, %53, %54, %55, %56, %57, %58, %59, %60, %61, %62, %63, %64, %65, %66, %67, %68, %69, %70, %71}, "
    "{%72, %73, %74, %75}, %76, 1, 1, 1, %77;"
    : "+f"(d[0]), "+f"(d[1]), "+f"(d[2]), "+f"(d[3]), "+f"(d[4]), "+f"(d[5]), "+f"(d[6]), "+f"(d[7]), "+f"(d[8]), "+f"(d[9]), "+f"(d[10]), "+f"(d[11]), "+f"(d[12]), "+f"(d[13]), "+f"(d[14]), "+f"(d[15]), "+f"(d[16]), "+f"(d[17]), "+f"(d[18]), "+f"(d[19]), "+f"(d[20]), "+f"(d[21]), "+f"(d[22]), "+f"(d[23]), "+f"(d[24]), "+f"(d[25]), "+f"(d[26]), "+f"(d[27]), "+f"(d[28]), "+f"(d[29]), "+f"(d[30]), "+f"(d[31]), "+f"(d[32]), "+f"(d[33]), "+f"(d[34]), "+f"(d[35]), "+f"(d[36]), "+f"(d[37]), "+f"(d[38]), "+f"(d[39]), "+f"(d[40]), "+f"(d[41]), "+f"(d[42]), "+f"(d[43]), "+f"(d[44]), "+f"(d[45]), "+f"(d[46]), "+f"(d[47]), "+f"(d[48]), "+f"(d[49]), "+f"(d[50]), "+f"(d[51]), "+f"(d[52]), "+f"(d[53]), "+f"(d[54]), "+f"(d[55]), "+f"(d[56]), "+f"(d[57]), "+f"(d[58]), "+f"(d[59]), "+f"(d[60]), "+f"(d[61]), "+f"(d[62]), "+f"(d[63]), "+f"(d[64]), "+f"(d[65]), "+f"(d[66]), "+f"(d[67]), "+f"(d[68]), "+f"(d[69]), "+f"(d[70]), "+f"(d[71])
    : "r"(a0), "r"(a1), "r"(a2), "r"(a3), "l"(desc), "n"(TB));
}
template <int TA, int TB> __device__ __forceinline__ void wgmma_ss_n96(float (&d)[48], uint64_t desca, uint64_t descb) {
  asm volatile("wgmma.mma_async.sync.aligned.m64n96k16.f32.bf16.bf16 "
    "{%0, %1, %2, %3, %4, %5, %6, %7, %8, %9, %10, %11, %12, %13, %14, %15, %16, %17, %18, %19, %20, %21, %22, %23, %24, %25, %26, %27, %28, %29, %30, %31, %32, %33, %34, %35, %36, %37, %38, %39, %40, %41, %42, %43, %44, %45, %46, %47}, "
    "%48, %49, 1, 1, 1, %50, %51;"
    : "+f"(d[0]), "+f"(d[1]), "+f"(d[2]), "+f"(d[3]), "+f"(d[4]), "+f"(d[5]), "+f"(d[6]), "+f"(d[7]), "+f"(d[8]), "+f"(d[9]), "+f"(d[10]), "+f"(d[11]), "+f"(d[12]), "+f"(d[13]), "+f"(d[14]), "+f"(d[15]), "+f"(d[16]), "+f"(d[17]), "+f"(d[18]), "+f"(d[19]), "+f"(d[20]), "+f"(d[21]), "+f"(d[22]), "+f"(d[23]), "+f"(d[24]), "+f"(d[25]), "+f"(d[26]), "+f"(d[27]), "+f"(d[28]), "+f"(d[29]), "+f"(d[30]), "+f"(d[31]), "+f"(d[32]), "+f"(d[33]), "+f"(d[34]), "+f"(d[35]), "+f"(d[36]), "+f"(d[37]), "+f"(d[38]), "+f"(d[39]), "+f"(d[40]), "+f"(d[41]), "+f"(d[42]), "+f"(d[43]), "+f"(d[44]), "+f"(d[45]), "+f"(d[46]), "+f"(d[47])
    : "l"(desca), "l"(descb), "n"(TA), "n"(TB));
}


__device__ __forceinline__ void wg_fence() { asm volatile("wgmma.fence.sync.aligned;" ::: "memory"); }
__device__ __forceinline__ void wg_commit() { asm volatile("wgmma.commit_group.sync.aligned;" ::: "memory"); }
template <int N> __device__ __forceinline__ void wg_wait() {
  asm volatile("wgmma.wait_group.sync.aligned %0;" ::"n"(N) : "memory");
}
template <int N> __device__ __forceinline__ void pin(float (&a)[N]) {
#pragma unroll
  for (int i = 0; i < N; i++) asm volatile("" : "+f"(a[i])::"memory");
}
__device__ __forceinline__ uint64_t make_desc(uint32_t addr, uint32_t lbo, uint32_t sbo) {
  uint32_t lo = ((addr & 0x3FFFF) >> 4) | ((lbo >> 4) << 16);
  uint32_t hi = sbo >> 4;
  return ((uint64_t)hi << 32) | lo;
}
__device__ __forceinline__ uint64_t make_desc_sw32(uint32_t addr, uint32_t lbo, uint32_t sbo) {
  return make_desc(addr, lbo, sbo) | (3ull << 62);
}
__device__ __forceinline__ uint64_t desc_add(uint64_t d, uint32_t bytes) { return d + (bytes >> 4); }

__device__ __forceinline__ uint32_t pack_bf16(float lo, float hi) {
  uint32_t r;
  asm("cvt.rn.bf16x2.f32 %0, %1, %2;" : "=r"(r) : "f"(hi), "f"(lo));
  return r;
}
__device__ __forceinline__ uint32_t pack_bf16_v(float lo, float hi) {
  uint32_t r;
  asm volatile("cvt.rn.bf16x2.f32 %0, %1, %2;" : "=r"(r) : "f"(hi), "f"(lo));
  return r;
}
__device__ __forceinline__ uint32_t bf2_add(uint32_t a, uint32_t b) {
  uint32_t r; asm("add.rn.bf16x2 %0, %1, %2;" : "=r"(r) : "r"(a), "r"(b)); return r;
}
__device__ __forceinline__ uint32_t bf2_sub(uint32_t a, uint32_t b) {
  uint32_t r; asm("sub.rn.bf16x2 %0, %1, %2;" : "=r"(r) : "r"(a), "r"(b)); return r;
}
__device__ __forceinline__ uint32_t bf2_fma(uint32_t a, uint32_t b, uint32_t c) {
  uint32_t r; asm("fma.rn.bf16x2 %0, %1, %2, %3;" : "=r"(r) : "r"(a), "r"(b), "r"(c)); return r;
}
__device__ __forceinline__ uint32_t bf2_max(uint32_t a, uint32_t b) {
  uint32_t r; asm("max.bf16x2 %0, %1, %2;" : "=r"(r) : "r"(a), "r"(b)); return r;
}
__device__ __forceinline__ uint32_t bf2_ex2(uint32_t a) {
  uint32_t r; asm("ex2.approx.ftz.bf16x2 %0, %1;" : "=r"(r) : "r"(a)); return r;
}
__device__ __forceinline__ float rcp_approx(float a) {
  float r; asm("rcp.approx.ftz.f32 %0, %1;" : "=f"(r) : "f"(a)); return r;
}
__device__ __forceinline__ uint64_t policy_evict_first() {
  uint64_t p;
  asm("createpolicy.fractional.L2::evict_first.b64 %0, 1.0;" : "=l"(p));
  return p;
}
__device__ __forceinline__ uint4 ldg_stream(const void* p) {
  uint4 v;
  asm volatile("ld.global.L1::no_allocate.L2::cache_hint.v4.b32 {%0,%1,%2,%3}, [%4], %5;"
               : "=r"(v.x), "=r"(v.y), "=r"(v.z), "=r"(v.w) : "l"(p), "l"(policy_evict_first()));
  return v;
}
__device__ __forceinline__ uint4 ldg_cached(const void* p) {
  uint4 v;
  asm volatile("ld.global.nc.v4.b32 {%0,%1,%2,%3}, [%4];"
               : "=r"(v.x), "=r"(v.y), "=r"(v.z), "=r"(v.w) : "l"(p));
  return v;
}
__device__ __forceinline__ void ldsm_x4(uint32_t addr, uint4& v) {
  asm volatile("ldmatrix.sync.aligned.m8n8.x4.shared.b16 {%0,%1,%2,%3}, [%4];"
               : "=r"(v.x), "=r"(v.y), "=r"(v.z), "=r"(v.w) : "r"(addr) : "memory");
}
__device__ __forceinline__ void tma_load_4d(uint32_t dst, const CUtensorMap* map, uint32_t bar, int c1, int c2) {
  asm volatile("cp.async.bulk.tensor.4d.shared::cluster.global.mbarrier::complete_tx::bytes.L2::cache_hint [%0], [%1, {%3, %4, %5, %3}], [%2], %6;"
               ::"r"(dst), "l"(map), "r"(bar), "r"(0), "r"(c1), "r"(c2), "l"(policy_evict_first()) : "memory");
}
__device__ __forceinline__ void tma_prefetch_4d(const CUtensorMap* map, int c1, int c2) {
  asm volatile("cp.async.bulk.prefetch.tensor.4d.L2.global.tile.L2::cache_hint [%0, {%1, %2, %3, %1}], %4;"
               ::"l"(map), "r"(0), "r"(c1), "r"(c2), "l"(policy_evict_first()) : "memory");
}
__device__ __forceinline__ void tma_store_4d(const CUtensorMap* map, uint32_t src, int c1, int c2, int c3) {
  asm volatile("cp.async.bulk.tensor.4d.global.shared::cta.bulk_group [%0, {%2, %3, %4, %5}], [%1];"
               ::"l"(map), "r"(src), "r"(0), "r"(c1), "r"(c2), "r"(c3) : "memory");
  asm volatile("cp.async.bulk.commit_group;" ::: "memory");
}
__device__ __forceinline__ void tma_store_wait_read() { asm volatile("cp.async.bulk.wait_group.read 0;" ::: "memory"); }
__device__ __forceinline__ void bulk_load(uint32_t dst, const void* src, uint32_t bytes, uint32_t bar) {
  asm volatile("cp.async.bulk.shared::cluster.global.mbarrier::complete_tx::bytes [%0], [%1], %2, [%3];"
               ::"r"(dst), "l"(src), "r"(bytes), "r"(bar) : "memory");
}
__device__ __forceinline__ void prefetch_l2(const void* p, uint32_t bytes) {
  asm volatile("cp.async.bulk.prefetch.L2.global.L2::cache_hint [%0], %1, %2;" ::"l"(p), "r"(bytes), "l"(policy_evict_first()) : "memory");
}
__device__ __forceinline__ void stsm_x4(uint32_t addr, uint32_t a, uint32_t b, uint32_t c, uint32_t d) {
  asm volatile("stmatrix.sync.aligned.m8n8.x4.shared.b16 [%0], {%1,%2,%3,%4};"
               ::"r"(addr), "r"(a), "r"(b), "r"(c), "r"(d) : "memory");
}
__device__ __forceinline__ void st_async_v2(uint32_t addr, uint32_t mbar, uint32_t a, uint32_t b) {
  asm volatile("st.async.weak.shared::cluster.mbarrier::complete_tx::bytes.v2.b32 [%0], {%1,%2}, [%3];"
               ::"r"(addr), "r"(a), "r"(b), "r"(mbar) : "memory");
}
__device__ __forceinline__ uint32_t mapa(uint32_t addr, uint32_t rank) {
  uint32_t r; asm("mapa.shared::cluster.u32 %0, %1, %2;" : "=r"(r) : "r"(addr), "r"(rank)); return r;
}
__device__ __forceinline__ void mbar_init(uint32_t bar, uint32_t count) {
  asm volatile("mbarrier.init.shared::cta.b64 [%0], %1;" ::"r"(bar), "r"(count) : "memory");
}
__device__ __forceinline__ void mbar_arrive_remote(uint32_t bar) {
  asm volatile("mbarrier.arrive.relaxed.cluster.shared::cluster.b64 _, [%0];" ::"r"(bar) : "memory");
}
__device__ __forceinline__ void mbar_expect_tx(uint32_t bar, uint32_t bytes) {
  asm volatile("mbarrier.arrive.expect_tx.shared::cta.b64 _, [%0], %1;" ::"r"(bar), "r"(bytes) : "memory");
}
__device__ __forceinline__ void mbar_wait(uint32_t bar, uint32_t parity) {
  asm volatile("{\n.reg .pred p, q;\n.reg .u32 c;\nmov.u32 c, 0;\n"
               "WAIT_LOOP:\n"
               "mbarrier.try_wait.parity.shared::cta.b64 p, [%0], %1;\n"
               "@p bra WAIT_DONE;\n"
               "add.u32 c, c, 1;\n"
               "setp.lt.u32 q, c, 0x1000000;\n"
               "@q bra WAIT_LOOP;\n"
               "trap;\n"
               "WAIT_DONE:\n}\n"
               ::"r"(bar), "r"(parity) : "memory");
}
__device__ __forceinline__ bool elect_one() {
  uint32_t p;
  asm volatile("{\n.reg .pred q;\nelect.sync _|q, 0xffffffff;\nselp.u32 %0, 1, 0, q;\n}\n" : "=r"(p));
  return p != 0;
}
__device__ __forceinline__ void wg_bar(int id) { asm volatile("bar.sync %0, 128;" ::"r"(id) : "memory"); }
__device__ __forceinline__ void fence_async_smem() { asm volatile("fence.proxy.async.shared::cta;" ::: "memory"); }

__device__ __forceinline__ void bias_mask(const uint4 (&b)[4], const uint4 (&mk)[4], uint32_t (&bm)[16]) {
#pragma unroll
  for (int i = 0; i < 4; i++) {
    bm[4 * i] = bf2_fma(mk[i].x, LOG2E_BF16X2, b[i].x);
    bm[4 * i + 1] = bf2_fma(mk[i].y, LOG2E_BF16X2, b[i].y);
    bm[4 * i + 2] = bf2_fma(mk[i].z, LOG2E_BF16X2, b[i].z);
    bm[4 * i + 3] = bf2_fma(mk[i].w, LOG2E_BF16X2, b[i].w);
  }
}
__device__ __forceinline__ void softmax_frag(const float (&s)[32], const uint32_t (&bm)[16],
                                             uint32_t (&pa)[8], uint32_t (&pb)[8]) {
#pragma unroll
  for (int j = 0; j < 8; j++) {
    pa[j] = bf2_add(pack_bf16(s[4 * j], s[4 * j + 1]), bm[j]);
    pb[j] = bf2_add(pack_bf16(s[4 * j + 2], s[4 * j + 3]), bm[8 + j]);
  }
  uint32_t xa = bf2_max(bf2_max(bf2_max(pa[0], pa[1]), bf2_max(pa[2], pa[3])),
                        bf2_max(bf2_max(pa[4], pa[5]), bf2_max(pa[6], pa[7])));
  uint32_t xb = bf2_max(bf2_max(bf2_max(pb[0], pb[1]), bf2_max(pb[2], pb[3])),
                        bf2_max(bf2_max(pb[4], pb[5]), bf2_max(pb[6], pb[7])));
  uint32_t m = bf2_max(__byte_perm(xa, xb, 0x5410), __byte_perm(xa, xb, 0x7632));
  m = bf2_max(m, __shfl_xor_sync(0xffffffffu, m, 1));
  m = bf2_max(m, __shfl_xor_sync(0xffffffffu, m, 2));
  const uint32_t mA = __byte_perm(m, m, 0x1010), mB = __byte_perm(m, m, 0x3232);
#pragma unroll
  for (int j = 0; j < 8; j++) {
    pa[j] = bf2_ex2(bf2_sub(pa[j], mA));
    pb[j] = bf2_ex2(bf2_sub(pb[j], mB));
  }
}
__device__ __forceinline__ void load_bias(const uint4* p, uint4 (&b)[4]) {
#pragma unroll
  for (int i = 0; i < 4; i++) b[i] = ldg_cached(p + 128 * i);
}

constexpr int PREP_PIECES = W_IMG / 16 + 1024;
__global__ void __launch_bounds__(256)
swin_prep_kernel(const __nv_bfloat16* __restrict__ wqkv, const __nv_bfloat16* __restrict__ wo,
                 const __nv_bfloat16* __restrict__ rpb, const int* __restrict__ rp_idx) {
  asm volatile("griddepcontrol.launch_dependents;");
  const int idx = blockIdx.x * 256 + threadIdx.x;
  const int rank = idx / PREP_PIECES;
  int pc = idx - rank * PREP_PIECES;
  if (rank >= 2) return;
  if (pc < (int)(SM_WO / 16)) {
    const int part = pc / 1152, rem = pc - part * 1152;
    const int grp = rem / 384, k = (rem - grp * 384) >> 1, hf = (rem & 1) ^ ((k >> 2) & 1);
    const int sect = (part == 0 || part == 2) ? 192 : (part == 1 || part == 5) ? 384 : 0;
    const int hh = (part == 2 || part == 4 || part == 5) ? 1 : 0;
    uint4 w = __ldg(reinterpret_cast<const uint4*>(wqkv + k * 576 + sect + (2 * rank + hh) * 48 + 16 * grp + 8 * hf));
    if (sect == 0) {
      uint32_t* u = reinterpret_cast<uint32_t*>(&w);
#pragma unroll
      for (int c = 0; c < 4; c++)
        u[c] = pack_bf16(__uint_as_float(u[c] << 16) * QSCALE, __uint_as_float(u[c] & 0xffff0000u) * QSCALE);
    }
    g_wimg[rank][pc] = w;
  } else if (pc < (int)(W_IMG / 16)) {
    const int q0 = pc - SM_WO / 16;
    const int half = q0 / 1152, rem = q0 - half * 1152;
    const int grp = rem / 192, k = (rem - grp * 192) >> 1, hf = (rem & 1) ^ ((k >> 2) & 1);
    int row = 96 * rank + k;
    if (half) {
      const int p = k >> 4, tt = (k >> 2) & 3, i = (k >> 1) & 1;
      row = 96 * (rank ^ 1) + 16 * p + 8 * i + 2 * tt + (k & 1);
    }
    g_wimg[rank][pc] = __ldg(reinterpret_cast<const uint4*>(wo + row * CH + 96 * rank + 16 * grp + 8 * hf));
  } else {
    pc -= W_IMG / 16;
    const int hh = pc >> 9, sel = (pc >> 8) & 1, u = (pc >> 7) & 1, wt = pc & 127;
    const int w4 = wt >> 5, gg = (wt & 31) >> 2, tt = wt & 3;
    const int row = 8 * ((gg >> 1) + 4 * (w4 >> 1)) + 4 * (w4 & 1) + (gg & 1) + 2 * sel;
    const int4* p = reinterpret_cast<const int4*>(rp_idx + row * 64 + 8 * (tt + 4 * u));
    if ((threadIdx.x & 31) < 15) asm volatile("prefetch.global.L1 [%0];" ::"l"(rpb + (threadIdx.x & 31) * 64));
    const int4 i0 = __ldg(p), i1 = __ldg(p + 1);
    const int head = 2 * rank + hh;
    auto bv = [&](int i) { return __bfloat162float(rpb[i * 4 + head]) * LOG2E; };
    g_bias[rank][pc] = make_uint4(pack_bf16(bv(i0.x), bv(i0.y)), pack_bf16(bv(i0.z), bv(i0.w)),
                                  pack_bf16(bv(i1.x), bv(i1.y)), pack_bf16(bv(i1.z), bv(i1.w)));
  }
}

__global__ void __cluster_dims__(2, 1, 1) __launch_bounds__(NTHREADS, 1)
swin_window_attn_kernel(const __grid_constant__ CUtensorMap xmap, const __grid_constant__ CUtensorMap ymap,
                        const __nv_bfloat16* __restrict__ mask) {
  extern __shared__ __align__(1024) uint8_t smem[];
  const uint32_t sbase = (uint32_t)__cvta_generic_to_shared(smem);
  const int tid = threadIdx.x;
  const int wg = __shfl_sync(0xffffffffu, tid >> 7, 0);
  const int wtid = tid & 127, lane = tid & 31;
  const int warp = __shfl_sync(0xffffffffu, wtid >> 5, 0);
  const int g = lane >> 2, t = lane & 3;
  uint32_t crank;
  asm("mov.u32 %0, %%cluster_ctarank;" : "=r"(crank));
  const int ncl = gridDim.x >> 1;
  const int cl = blockIdx.x >> 1;

  const int th = (g >> 1) + 4 * (warp >> 1);
  const int tw = 4 * (warp & 1) + (g & 1);
  const int wstride = ncl * NWG;
  int win = wg * ncl + cl;

  const uint32_t bar_rdy = sbase + SM_BAR + wg * 32;
  const uint32_t bar_dat = bar_rdy + 16;
  const uint32_t bar_x0 = sbase + SM_BAR + 96;
  const uint32_t x_quad = sbase + SM_X + warp * X_QUAD;
  auto quad_coords = [&](int w, int& y, int& x) {
    const int wi = w / 48, wj = w - wi * 48;
    y = wi * 8 + 4 + 4 * (warp >> 1);
    x = wj * 8 + 4 + 4 * (warp & 1);
    if (y >= IMG) y -= IMG;
    if (x >= IMG) x -= IMG;
  };
  auto issue_x = [&](int w, int dst_wg) {
    int y, x;
    quad_coords(w, y, x);
    const uint32_t bar = bar_x0 + (dst_wg * 4 + warp) * 8;
    mbar_expect_tx(bar, X_QUAD);
    tma_load_4d(x_quad, &xmap, bar, y, x);
    if ((warp & 1) == crank && w + PF_DIST * ncl < NWIN) {
      quad_coords(w + PF_DIST * ncl, y, x);
      tma_prefetch_4d(&xmap, y, x);
    }
  };

  const uint32_t bar_w = bar_x0 + 96;
  const uint32_t wgbuf = sbase + SM_WG + wg * WG_BYTES;
  const uint64_t d_wqkv = make_desc_sw32(sbase + SM_WQKV, 6144, 256);
  const uint64_t d_wo = make_desc_sw32(sbase + SM_WO, 3072, 256);
  const uint64_t d_k = make_desc(wgbuf, 1024, 128);
  const uint64_t d_v = make_desc(wgbuf, 128, 1024);
  const uint64_t d_ex = make_desc_sw32(wgbuf, 16, 256);
  if (tid == 0) {
#pragma unroll
    for (int i = 0; i < NWG; i++) {
      mbar_init(sbase + SM_BAR + i * 32, 4);
      mbar_init(sbase + SM_BAR + i * 32 + 8, 4);
      mbar_init(sbase + SM_BAR + i * 32 + 16, 1);
      mbar_init(sbase + SM_BAR + i * 32 + 24, 1);
    }
#pragma unroll
    for (int i = 0; i < 4 * NWG; i++) mbar_init(bar_x0 + i * 8, 1);
    mbar_init(bar_w, 1);
    asm volatile("fence.mbarrier_init.release.cluster;" ::: "memory");
    fence_async_smem();
  }
  *reinterpret_cast<uint2*>(smem + SM_WG + wg * WG_BYTES + OFF_ONES + wtid * 8) = make_uint2(0x3F803F80u, 0x3F803F80u);
  fence_async_smem();
  __syncthreads();
  asm volatile("barrier.cluster.arrive.relaxed.aligned;" ::: "memory");
  if (wg == 0 && lane == 0 && win < NWIN) issue_x(win, 0);
  asm volatile("griddepcontrol.wait;" ::: "memory");
  if (tid == 0) {
    mbar_expect_tx(bar_w, W_IMG);
    const uint8_t* img = reinterpret_cast<const uint8_t*>(g_wimg[crank]);
#pragma unroll
    for (int i = 0; i < 8; i++) bulk_load(sbase + i * (W_IMG / 8), img + i * (W_IMG / 8), W_IMG / 8, bar_w);
  }
  asm volatile("barrier.cluster.wait.acquire.aligned;" ::: "memory");

  const int mi = lane >> 3, r8 = lane & 7;
  const uint32_t t_st = wgbuf + (mi >> 1) * 1024 + (2 * warp + (mi & 1)) * 128 + r8 * 16;
  const uint32_t ex_remote = mapa(wgbuf + (16 * warp + g) * 32 + (((t >> 1) ^ (g >> 2)) << 4) + (t & 1) * 8, crank ^ 1);
  const uint32_t dat_remote = mapa(bar_dat, crank ^ 1);
  const uint32_t rdy_remote = mapa(bar_rdy, crank ^ 1);
  const uint4* bias_ptr = &g_bias[crank][wtid];
  const uint32_t y_quad = wgbuf + warp * 3072;
  const uint32_t y_st = [&] {
    const int gg = lane & 7, sel = (lane >> 3) & 1, chi = lane >> 4;
    const int r = (2 * sel + (gg & 1)) * 4 + (gg >> 1);
    return y_quad + r * 64 + ((chi ^ ((r >> 1) & 3)) << 4);
  }();

  const uint32_t x_ld = [&] {
    const int gg = lane & 7, sel = (lane >> 3) & 1, khi = lane >> 4;
    const int r = (2 * sel + (gg & 1)) * 4 + (gg >> 1);
    return x_quad + r * 128 + ((khi ^ (r & 7)) << 4);
  }();
  const uint32_t bar_x = bar_x0 + (wg * 4 + warp) * 8;
  const int next_wg = wg == NWG - 1 ? 0 : wg + 1;
  const uint32_t mask_off = ((8 * th + tw) * 64 + 8 * t) * 2;

  uint4 xa[12];
  auto load_x_frags = [&](bool valid, uint32_t par) {
    if (valid) mbar_wait(bar_x, par);
#pragma unroll
    for (int s = 0; s < 12; s++) ldsm_x4((x_ld ^ ((s & 3) << 5)) + (s >> 2) * 2048, xa[s]);
  };
  load_x_frags(win < NWIN, 0);

  uint4 b0[4];
  load_bias(bias_ptr, b0);
  mbar_wait(bar_w, 0);
  uint32_t parity = 0;
  for (; win < NWIN; win += wstride, parity ^= 1) {
    uint4 mk[4];
    {
      float acc[72];
      wg_fence();
#pragma unroll
      for (int s = 0; s < 12; s++) {
        if (s == 0) wgmma_rs_n144_init<1>(acc, xa[s].x, xa[s].y, xa[s].z, xa[s].w, desc_add(d_wqkv, s * 512));
        else        wgmma_rs_n144<1>(acc, xa[s].x, xa[s].y, xa[s].z, xa[s].w, desc_add(d_wqkv, s * 512));
      }
      wg_commit();
      if (win + ncl < NWIN && elect_one()) issue_x(win + ncl, next_wg);
      if (warp == 0 && crank == 0 && win + wstride < NWIN && elect_one()) prefetch_l2(mask + (size_t)(win + wstride) * 4096, 8192);
      tma_store_wait_read();
      wg_bar(1 + wg);
      const __nv_bfloat16* mp = reinterpret_cast<const __nv_bfloat16*>(reinterpret_cast<const uint8_t*>(mask + (size_t)win * 4096) + mask_off);
      mk[0] = ldg_stream(mp);
      mk[1] = ldg_stream(mp + 32);
      mk[2] = ldg_stream(mp + 128);
      mk[3] = ldg_stream(mp + 160);
      wg_wait<0>();
      pin(acc);
#pragma unroll
      for (int j = 0; j < 18; j += 2) {
        const uint32_t off = (j < 6 ? OFF_K0 : j < 12 ? OFF_V0 : OFF_K1) + (j % 6) * 1024;
        stsm_x4(t_st + off, pack_bf16(acc[4 * j], acc[4 * j + 1]), pack_bf16(acc[4 * j + 2], acc[4 * j + 3]),
                pack_bf16(acc[4 * j + 4], acc[4 * j + 5]), pack_bf16(acc[4 * j + 6], acc[4 * j + 7]));
      }
      fence_async_smem();
    }
    float s0[32], s1[32];
    uint32_t v1[12];
    uint32_t bm[16];
    {
      float acc[72];
      wg_fence();
#pragma unroll
      for (int s = 0; s < 12; s++) {
        if (s == 0) wgmma_rs_n144_init<1>(acc, xa[s].x, xa[s].y, xa[s].z, xa[s].w, desc_add(d_wqkv, WQKV_HEAD + s * 512));
        else        wgmma_rs_n144<1>(acc, xa[s].x, xa[s].y, xa[s].z, xa[s].w, desc_add(d_wqkv, WQKV_HEAD + s * 512));
      }
      wg_commit();
      wg_bar(1 + wg);
      wg_wait<0>();
      pin(acc);
      uint32_t qa[12], qb[12];
#pragma unroll
      for (int j = 0; j < 12; j++) {
        qa[j] = pack_bf16(acc[4 * j], acc[4 * j + 1]);
        qb[j] = pack_bf16(acc[4 * j + 2], acc[4 * j + 3]);
      }
#pragma unroll
      for (int j = 0; j < 12; j++) v1[j] = pack_bf16(acc[48 + 2 * j], acc[48 + 2 * j + 1]);
      wg_fence();
#pragma unroll
      for (int k = 0; k < 3; k++) {
        if (k == 0) wgmma_rs_n64_init<0>(s0, qa[0], qb[0], qa[1], qb[1], desc_add(d_k, OFF_K0));
        else        wgmma_rs_n64<0>(s0, qa[2 * k], qb[2 * k], qa[2 * k + 1], qb[2 * k + 1], desc_add(d_k, OFF_K0 + k * 2048));
      }
      wg_commit();
#pragma unroll
      for (int k = 0; k < 3; k++) {
        if (k == 0) wgmma_rs_n64_init<0>(s1, qa[6], qb[6], qa[7], qb[7], desc_add(d_k, OFF_K1));
        else        wgmma_rs_n64<0>(s1, qa[6 + 2 * k], qb[6 + 2 * k], qa[7 + 2 * k], qb[7 + 2 * k], desc_add(d_k, OFF_K1 + k * 2048));
      }
      wg_commit();
      bias_mask(b0, mk, bm);
      wg_wait<1>();
      pin(s0);
    }
    uint32_t pa[8], pb[8];
    float o0[28];
    wg_bar(1 + wg);
#pragma unroll
    for (int j = 0; j < 3; j++) stsm_x4(t_st + OFF_K0 + j * 2048, v1[4 * j], v1[4 * j + 1], v1[4 * j + 2], v1[4 * j + 3]);
    fence_async_smem();
    uint4 b1[4];
    load_bias(bias_ptr + 512, b1);
    softmax_frag(s0, bm, pa, pb);
    wg_fence();
#pragma unroll
    for (int k = 0; k < 4; k++) {
      if (k == 0) wgmma_rs_n56_init<1>(o0, pa[0], pb[0], pa[1], pb[1], desc_add(d_v, OFF_V0));
      else        wgmma_rs_n56<1>(o0, pa[2 * k], pb[2 * k], pa[2 * k + 1], pb[2 * k + 1], desc_add(d_v, OFF_V0 + k * 256));
    }
    wg_commit();
    bias_mask(b1, mk, bm);
    wg_wait<1>();
    pin(s1);
    if (elect_one()) mbar_arrive_remote(rdy_remote);
    if (warp == 0 && elect_one()) {
      mbar_expect_tx(bar_dat, 64 * 48 * 2);
      mbar_expect_tx(bar_dat + 8, 64 * 48 * 2);
    }
    uint32_t pc[8], pd[8];
    softmax_frag(s1, bm, pc, pd);
    wg_wait<0>();
    pin(o0);
    if (elect_one()) mbar_arrive_remote(rdy_remote + 8);
    wg_bar(1 + wg);
    float o1[28];
    wg_fence();
#pragma unroll
    for (int k = 0; k < 4; k++) {
      if (k == 0) wgmma_rs_n56_init<1>(o1, pc[0], pd[0], pc[1], pd[1], desc_add(d_v, OFF_ONES));
      else        wgmma_rs_n56<1>(o1, pc[2 * k], pd[2 * k], pc[2 * k + 1], pd[2 * k + 1], desc_add(d_v, OFF_ONES + k * 256));
    }
    wg_commit();
    uint32_t oa[12], ob[12], sa[12], sb[12];
    float acc[48];
    {
      const float ra = rcp_approx(o0[24]), rb = rcp_approx(o0[26]);
#pragma unroll
      for (int j = 0; j < 6; j++) {
        const float a0 = o0[4 * j] * ra, a1 = o0[4 * j + 1] * ra, c0 = o0[4 * j + 2] * rb, c1 = o0[4 * j + 3] * rb;
        oa[j] = pack_bf16(a0, a1);
        ob[j] = pack_bf16(c0, c1);
        sa[j] = pack_bf16_v(a0, a1);
        sb[j] = pack_bf16_v(c0, c1);
      }
    }
    mbar_wait(bar_rdy, parity);
#pragma unroll
    for (int p = 0; p < 3; p++) {
      st_async_v2(ex_remote + OFF_K1 + p * 2048, dat_remote, sa[2 * p], sa[2 * p + 1]);
      st_async_v2(ex_remote + OFF_K1 + p * 2048 + 256, dat_remote, sb[2 * p], sb[2 * p + 1]);
    }
    wg_fence();
#pragma unroll
    for (int s = 0; s < 3; s++) {
      if (s == 0) wgmma_rs_n96_init<1>(acc, oa[0], ob[0], oa[1], ob[1], d_wo);
      else        wgmma_rs_n96<1>(acc, oa[2 * s], ob[2 * s], oa[2 * s + 1], ob[2 * s + 1], desc_add(d_wo, s * 512));
    }
    wg_commit();
    wg_wait<1>();
    pin(o1);
    {
      const float ra = rcp_approx(o1[0]), rb = rcp_approx(o1[2]);
#pragma unroll
      for (int j = 0; j < 6; j++) {
        const float a0 = o1[4 + 4 * j] * ra, a1 = o1[4 + 4 * j + 1] * ra, c0 = o1[4 + 4 * j + 2] * rb, c1 = o1[4 + 4 * j + 3] * rb;
        oa[6 + j] = pack_bf16(a0, a1);
        ob[6 + j] = pack_bf16(c0, c1);
        sa[6 + j] = pack_bf16_v(a0, a1);
        sb[6 + j] = pack_bf16_v(c0, c1);
      }
    }
    mbar_wait(bar_rdy + 8, parity);
#pragma unroll
    for (int p = 0; p < 3; p++) {
      st_async_v2(ex_remote + OFF_V0 + p * 2048, dat_remote + 8, sa[6 + 2 * p], sa[6 + 2 * p + 1]);
      st_async_v2(ex_remote + OFF_V0 + p * 2048 + 256, dat_remote + 8, sb[6 + 2 * p], sb[6 + 2 * p + 1]);
    }
    wg_fence();
#pragma unroll
    for (int s = 3; s < 6; s++)
      wgmma_rs_n96<1>(acc, oa[2 * s], ob[2 * s], oa[2 * s + 1], ob[2 * s + 1], desc_add(d_wo, s * 512));
    wg_commit();
    mbar_wait(bar_dat, parity);
    fence_async_smem();
    wg_fence();
#pragma unroll
    for (int s = 0; s < 3; s++)
      wgmma_ss_n96<0, 1>(acc, desc_add(d_ex, s * 2048), desc_add(d_wo, WO_HALF + s * 512));
    wg_commit();
    mbar_wait(bar_dat + 8, parity);
    fence_async_smem();
    wg_fence();
#pragma unroll
    for (int s = 3; s < 6; s++)
      wgmma_ss_n96<0, 1>(acc, desc_add(d_ex, s * 2048), desc_add(d_wo, WO_HALF + s * 512));
    wg_commit();
    load_x_frags(win + wstride < NWIN, parity ^ 1);
    wg_wait<0>();
    pin(acc);
    wg_bar(1 + wg);
#pragma unroll
    for (int j = 0; j < 12; j += 2)
      stsm_x4((y_st ^ ((j & 2) << 4)) + (j >> 2) * 1024, pack_bf16(acc[4 * j], acc[4 * j + 1]), pack_bf16(acc[4 * j + 2], acc[4 * j + 3]),
              pack_bf16(acc[4 * j + 4], acc[4 * j + 5]), pack_bf16(acc[4 * j + 6], acc[4 * j + 7]));
    fence_async_smem();
    __syncwarp();
    if (elect_one()) {
      const int wi = win / 48, wj = win - wi * 48;
      int y = wi * 8 + 4 + 4 * (warp >> 1), x = wj * 8 + 4 + 4 * (warp & 1);
      if (y >= IMG) y -= IMG;
      if (x >= IMG) x -= IMG;
      tma_store_4d(&ymap, y_quad, y, x, 3 * crank);
    }
  }
  tma_store_wait_read();
  asm volatile("barrier.cluster.arrive.release.aligned;\nbarrier.cluster.wait.acquire.aligned;" ::: "memory");
}

}

extern "C" void kernel_launch(void* const* d_in, const int* in_sizes, int n_in, void* d_out, int out_size) {
  (void)in_sizes; (void)n_in; (void)out_size;
  typedef CUresult (*EncodeFn)(CUtensorMap*, CUtensorMapDataType, cuuint32_t, void*, const cuuint64_t*, const cuuint64_t*,
                               const cuuint32_t*, const cuuint32_t*, CUtensorMapInterleave, CUtensorMapSwizzle,
                               CUtensorMapL2promotion, CUtensorMapFloatOOBfill);
  static int grid = 0;
  static EncodeFn encode = nullptr;
  if (grid == 0) {
    int dev = 0, sms = 0;
    cudaGetDevice(&dev);
    cudaDeviceGetAttribute(&sms, cudaDevAttrMultiProcessorCount, dev);
    cudaFuncSetAttribute(swin::swin_window_attn_kernel, cudaFuncAttributeMaxDynamicSharedMemorySize, swin::SM_TOTAL);
    void* fn = nullptr;
    cudaDriverEntryPointQueryResult qr;
    cudaGetDriverEntryPoint("cuTensorMapEncodeTiled", &fn, cudaEnableDefault, &qr);
    encode = (EncodeFn)fn;
    grid = sms & ~1;
  }
  CUtensorMap xmap;
  const cuuint64_t dims[4] = {64, 384, 384, 3};
  const cuuint64_t strides[3] = {384ull * 384ull, 384, 128};
  const cuuint32_t box[4] = {64, 4, 4, 3};
  const cuuint32_t estr[4] = {1, 1, 1, 1};
  encode(&xmap, CU_TENSOR_MAP_DATA_TYPE_BFLOAT16, 4, d_in[0], dims, strides, box, estr, CU_TENSOR_MAP_INTERLEAVE_NONE,
         CU_TENSOR_MAP_SWIZZLE_128B, CU_TENSOR_MAP_L2_PROMOTION_NONE, CU_TENSOR_MAP_FLOAT_OOB_FILL_NONE);
  CUtensorMap ymap;
  const cuuint64_t ydims[4] = {32, 384, 384, 6};
  const cuuint64_t ystrides[3] = {384ull * 384ull, 384, 64};
  const cuuint32_t ybox[4] = {32, 4, 4, 3};
  encode(&ymap, CU_TENSOR_MAP_DATA_TYPE_BFLOAT16, 4, d_out, ydims, ystrides, ybox, estr, CU_TENSOR_MAP_INTERLEAVE_NONE,
         CU_TENSOR_MAP_SWIZZLE_64B, CU_TENSOR_MAP_L2_PROMOTION_NONE, CU_TENSOR_MAP_FLOAT_OOB_FILL_NONE);
  swin::swin_prep_kernel<<<(2 * swin::PREP_PIECES + 255) / 256, 256, 0, cudaStreamPerThread>>>(
      (const __nv_bfloat16*)d_in[1], (const __nv_bfloat16*)d_in[2], (const __nv_bfloat16*)d_in[3], (const int*)d_in[4]);
  cudaLaunchConfig_t cfg = {};
  cfg.gridDim = dim3(grid);
  cfg.blockDim = dim3(swin::NTHREADS);
  cfg.dynamicSmemBytes = swin::SM_TOTAL;
  cfg.stream = cudaStreamPerThread;
  cudaLaunchAttribute attr[1];
  attr[0].id = cudaLaunchAttributeProgrammaticStreamSerialization;
  attr[0].val.programmaticStreamSerializationAllowed = 1;
  cfg.attrs = attr;
  cfg.numAttrs = 1;
  cudaLaunchKernelEx(&cfg, swin::swin_window_attn_kernel, xmap, ymap, (const __nv_bfloat16*)d_in[5]);
}
```

```cpp
#include <cuda_runtime.h>
#include <cuda_bf16.h>
#include <cuda.h>
#include <stdint.h>

namespace swin {

constexpr int IMG = 384;
constexpr int CH = 192;
constexpr int NWIN = 48 * 48;
constexpr int NWG = 3;
constexpr int NTHREADS = NWG * 128;
constexpr int PF_DIST = 1;

constexpr uint32_t SM_WQKV = 0;
constexpr uint32_t W_PART = 3 * 192 * 32;
constexpr uint32_t WQKV_HEAD = 3 * W_PART;
constexpr uint32_t SM_WO = 2 * WQKV_HEAD;
constexpr uint32_t WO_HALF = 6 * 96 * 32;
constexpr uint32_t SM_X = SM_WO + 2 * WO_HALF;
constexpr uint32_t X_QUAD = 3 * 16 * 128;
constexpr uint32_t SM_WG = SM_X + 4 * X_QUAD;
constexpr uint32_t OFF_K1 = 0;
constexpr uint32_t OFF_V0 = 6144;
constexpr uint32_t OFF_ONES = OFF_V0 + 6144;
constexpr uint32_t OFF_K0 = OFF_ONES + 1024;
constexpr uint32_t WG_BYTES = OFF_K0 + 6144;
constexpr uint32_t SM_BAR = SM_WG + NWG * WG_BYTES;
constexpr uint32_t SM_TOTAL = SM_BAR + 8 * (12 + 12 + 1);
static_assert(SM_X % 1024 == 0, "X stage must be swizzle-atom aligned");
static_assert(SM_TOTAL <= 232448, "shared memory budget");

constexpr float LOG2E = 1.4426950408889634f;
constexpr float QSCALE = 0.14433756729740643f * LOG2E;
constexpr uint32_t LOG2E_BF16X2 = 0x3FB93FB9u;

constexpr uint32_t W_IMG = SM_X;
__device__ __align__(128) uint4 g_wimg[2][W_IMG / 16];
__device__ uint4 g_bias[2][1024];

template <int TB> __device__ __forceinline__ void wgmma_rs_n56_init(float (&d)[28], uint32_t a0, uint32_t a1, uint32_t a2, uint32_t a3, uint64_t desc) {
  asm volatile("wgmma.mma_async.sync.aligned.m64n56k16.f32.bf16.bf16 "
    "{%0, %1, %2, %3, %4, %5, %6, %7, %8, %9, %10, %11, %12, %13, %14, %15, %16, %17, %18, %19, %20, %21, %22, %23, %24, %25, %26, %27}, "
    "{%28, %29, %30, %31}, %32, 0, 1, 1, %33;"
    : "=f"(d[0]), "=f"(d[1]), "=f"(d[2]), "=f"(d[3]), "=f"(d[4]), "=f"(d[5]), "=f"(d[6]), "=f"(d[7]), "=f"(d[8]), "=f"(d[9]), "=f"(d[10]), "=f"(d[11]), "=f"(d[12]), "=f"(d[13]), "=f"(d[14]), "=f"(d[15]), "=f"(d[16]), "=f"(d[17]), "=f"(d[18]), "=f"(d[19]), "=f"(d[20]), "=f"(d[21]), "=f"(d[22]), "=f"(d[23]), "=f"(d[24]), "=f"(d[25]), "=f"(d[26]), "=f"(d[27])
    : "r"(a0), "r"(a1), "r"(a2), "r"(a3), "l"(desc), "n"(TB));
}
template <int TB> __device__ __forceinline__ void wgmma_rs_n56(float (&d)[28], uint32_t a0, uint32_t a1, uint32_t a2, uint32_t a3, uint64_t desc) {
  asm volatile("wgmma.mma_async.sync.aligned.m64n56k16.f32.bf16.bf16 "
    "{%0, %1, %2, %3, %4, %5, %6, %7, %8, %9, %10, %11, %12, %13, %14, %15, %16, %17, %18, %19, %20, %21, %22, %23, %24, %25, %26, %27}, "
    "{%28, %29, %30, %31}, %32, 1, 1, 1, %33;"
    : "+f"(d[0]), "+f"(d[1]), "+f"(d[2]), "+f"(d[3]), "+f"(d[4]), "+f"(d[5]), "+f"(d[6]), "+f"(d[7]), "+f"(d[8]), "+f"(d[9]), "+f"(d[10]), "+f"(d[11]), "+f"(d[12]), "+f"(d[13]), "+f"(d[14]), "+f"(d[15]), "+f"(d[16]), "+f"(d[17]), "+f"(d[18]), "+f"(d[19]), "+f"(d[20]), "+f"(d[21]), "+f"(d[22]), "+f"(d[23]), "+f"(d[24]), "+f"(d[25]), "+f"(d[26]), "+f"(d[27])
    : "r"(a0), "r"(a1), "r"(a2), "r"(a3), "l"(desc), "n"(TB));
}
template <int TB> __device__ __forceinline__ void wgmma_rs_n64_init(float (&d)[32], uint32_t a0, uint32_t a1, uint32_t a2, uint32_t a3, uint64_t desc) {
  asm volatile("wgmma.mma_async.sync.aligned.m64n64k16.f32.bf16.bf16 "
    "{%0, %1, %2, %3, %4, %5, %6, %7, %8, %9, %10, %11, %12, %13, %14, %15, %16, %17, %18, %19, %20, %21, %22, %23, %24, %25, %26, %27, %28, %29, %30, %31}, "
    "{%32, %33, %34, %35}, %36, 0, 1, 1, %37;"
    : "=f"(d[0]), "=f"(d[1]), "=f"(d[2]), "=f"(d[3]), "=f"(d[4]), "=f"(d[5]), "=f"(d[6]), "=f"(d[7]), "=f"(d[8]), "=f"(d[9]), "=f"(d[10]), "=f"(d[11]), "=f"(d[12]), "=f"(d[13]), "=f"(d[14]), "=f"(d[15]), "=f"(d[16]), "=f"(d[17]), "=f"(d[18]), "=f"(d[19]), "=f"(d[20]), "=f"(d[21]), "=f"(d[22]), "=f"(d[23]), "=f"(d[24]), "=f"(d[25]), "=f"(d[26]), "=f"(d[27]), "=f"(d[28]), "=f"(d[29]), "=f"(d[30]), "=f"(d[31])
    : "r"(a0), "r"(a1), "r"(a2), "r"(a3), "l"(desc), "n"(TB));
}
template <int TB> __device__ __forceinline__ void wgmma_rs_n64(float (&d)[32], uint32_t a0, uint32_t a1, uint32_t a2, uint32_t a3, uint64_t desc) {
  asm volatile("wgmma.mma_async.sync.aligned.m64n64k16.f32.bf16.bf16 "
    "{%0, %1, %2, %3, %4, %5, %6, %7, %8, %9, %10, %11, %12, %13, %14, %15, %16, %17, %18, %19, %20, %21, %22, %23, %24, %25, %26, %27, %28, %29, %30, %31}, "
    "{%32, %33, %34, %35}, %36, 1, 1, 1, %37;"
    : "+f"(d[0]), "+f"(d[1]), "+f"(d[2]), "+f"(d[3]), "+f"(d[4]), "+f"(d[5]), "+f"(d[6]), "+f"(d[7]), "+f"(d[8]), "+f"(d[9]), "+f"(d[10]), "+f"(d[11]), "+f"(d[12]), "+f"(d[13]), "+f"(d[14]), "+f"(d[15]), "+f"(d[16]), "+f"(d[17]), "+f"(d[18]), "+f"(d[19]), "+f"(d[20]), "+f"(d[21]), "+f"(d[22]), "+f"(d[23]), "+f"(d[24]), "+f"(d[25]), "+f"(d[26]), "+f"(d[27]), "+f"(d[28]), "+f"(d[29]), "+f"(d[30]), "+f"(d[31])
    : "r"(a0), "r"(a1), "r"(a2), "r"(a3), "l"(desc), "n"(TB));
}
template <int TB> __device__ __forceinline__ void wgmma_rs_n96_init(float (&d)[48], uint32_t a0, uint32_t a1, uint32_t a2, uint32_t a3, uint64_t desc) {
  asm volatile("wgmma.mma_async.sync.aligned.m64n96k16.f32.bf16.bf16 "
    "{%0, %1, %2, %3, %4, %5, %6, %7, %8, %9, %10, %11, %12, %13, %14, %15, %16, %17, %18, %19, %20, %21, %22, %23, %24, %25, %26, %27, %28, %29, %30, %31, %32, %33, %34, %35, %36, %37, %38, %39, %40, %41, %42, %43, %44, %45, %46, %47}, "
    "{%48, %49, %50, %51}, %52, 0, 1, 1, %53;"
    : "=f"(d[0]), "=f"(d[1]), "=f"(d[2]), "=f"(d[3]), "=f"(d[4]), "=f"(d[5]), "=f"(d[6]), "=f"(d[7]), "=f"(d[8]), "=f"(d[9]), "=f"(d[10]), "=f"(d[11]), "=f"(d[12]), "=f"(d[13]), "=f"(d[14]), "=f"(d[15]), "=f"(d[16]), "=f"(d[17]), "=f"(d[18]), "=f"(d[19]), "=f"(d[20]), "=f"(d[21]), "=f"(d[22]), "=f"(d[23]), "=f"(d[24]), "=f"(d[25]), "=f"(d[26]), "=f"(d[27]), "=f"(d[28]), "=f"(d[29]), "=f"(d[30]), "=f"(d[31]), "=f"(d[32]), "=f"(d[33]), "=f"(d[34]), "=f"(d[35]), "=f"(d[36]), "=f"(d[37]), "=f"(d[38]), "=f"(d[39]), "=f"(d[40]), "=f"(d[41]), "=f"(d[42]), "=f"(d[43]), "=f"(d[44]), "=f"(d[45]), "=f"(d[46]), "=f"(d[47])
    : "r"(a0), "r"(a1), "r"(a2), "r"(a3), "l"(desc), "n"(TB));
}
template <int TB> __device__ __forceinline__ void wgmma_rs_n96(float (&d)[48], uint32_t a0, uint32_t a1, uint32_t a2, uint32_t a3, uint64_t desc) {
  asm volatile("wgmma.mma_async.sync.aligned.m64n96k16.f32.bf16.bf16 "
    "{%0, %1, %2, %3, %4, %5, %6, %7, %8, %9, %10, %11, %12, %13, %14, %15, %16, %17, %18, %19, %20, %21, %22, %23, %24, %25, %26, %27, %28, %29, %30, %31, %32, %33, %34, %35, %36, %37, %38, %39, %40, %41, %42, %43, %44, %45, %46, %47}, "
    "{%48, %49, %50, %51}, %52, 1, 1, 1, %53;"
    : "+f"(d[0]), "+f"(d[1]), "+f"(d[2]), "+f"(d[3]), "+f"(d[4]), "+f"(d[5]), "+f"(d[6]), "+f"(d[7]), "+f"(d[8]), "+f"(d[9]), "+f"(d[10]), "+f"(d[11]), "+f"(d[12]), "+f"(d[13]), "+f"(d[14]), "+f"(d[15]), "+f"(d[16]), "+f"(d[17]), "+f"(d[18]), "+f"(d[19]), "+f"(d[20]), "+f"(d[21]), "+f"(d[22]), "+f"(d[23]), "+f"(d[24]), "+f"(d[25]), "+f"(d[26]), "+f"(d[27]), "+f"(d[28]), "+f"(d[29]), "+f"(d[30]), "+f"(d[31]), "+f"(d[32]), "+f"(d[33]), "+f"(d[34]), "+f"(d[35]), "+f"(d[36]), "+f"(d[37]), "+f"(d[38]), "+f"(d[39]), "+f"(d[40]), "+f"(d[41]), "+f"(d[42]), "+f"(d[43]), "+f"(d[44]), "+f"(d[45]), "+f"(d[46]), "+f"(d[47])
    : "r"(a0), "r"(a1), "r"(a2), "r"(a3), "l"(desc), "n"(TB));
}
template <int TB> __device__ __forceinline__ void wgmma_rs_n144_init(float (&d)[72], uint32_t a0, uint32_t a1, uint32_t a2, uint32_t a3, uint64_t desc) {
  asm volatile("wgmma.mma_async.sync.aligned.m64n144k16.f32.bf16.bf16 "
    "{%0, %1, %2, %3, %4, %5, %6, %7, %8, %9, %10, %11, %12, %13, %14, %15, %16, %17, %18, %19, %20, %21, %22, %23, %24, %25, %26, %27, %28, %29, %30, %31, %32, %33, %34, %35, %36, %37, %38, %39, %40, %41, %42, %43, %44, %45, %46, %47, %48, %49, %50, %51, %52, %53, %54, %55, %56, %57, %58, %59, %60, %61, %62, %63, %64, %65, %66, %67, %68, %69, %70, %71}, "
    "{%72, %73, %74, %75}, %76, 0, 1, 1, %77;"
    : "=f"(d[0]), "=f"(d[1]), "=f"(d[2]), "=f"(d[3]), "=f"(d[4]), "=f"(d[5]), "=f"(d[6]), "=f"(d[7]), "=f"(d[8]), "=f"(d[9]), "=f"(d[10]), "=f"(d[11]), "=f"(d[12]), "=f"(d[13]), "=f"(d[14]), "=f"(d[15]), "=f"(d[16]), "=f"(d[17]), "=f"(d[18]), "=f"(d[19]), "=f"(d[20]), "=f"(d[21]), "=f"(d[22]), "=f"(d[23]), "=f"(d[24]), "=f"(d[25]), "=f"(d[26]), "=f"(d[27]), "=f"(d[28]), "=f"(d[29]), "=f"(d[30]), "=f"(d[31]), "=f"(d[32]), "=f"(d[33]), "=f"(d[34]), "=f"(d[35]), "=f"(d[36]), "=f"(d[37]), "=f"(d[38]), "=f"(d[39]), "=f"(d[40]), "=f"(d[41]), "=f"(d[42]), "=f"(d[43]), "=f"(d[44]), "=f"(d[45]), "=f"(d[46]), "=f"(d[47]), "=f"(d[48]), "=f"(d[49]), "=f"(d[50]), "=f"(d[51]), "=f"(d[52]), "=f"(d[53]), "=f"(d[54]), "=f"(d[55]), "=f"(d[56]), "=f"(d[57]), "=f"(d[58]), "=f"(d[59]), "=f"(d[60]), "=f"(d[61]), "=f"(d[62]), "=f"(d[63]), "=f"(d[64]), "=f"(d[65]), "=f"(d[66]), "=f"(d[67]), "=f"(d[68]), "=f"(d[69]), "=f"(d[70]), "=f"(d[71])
    : "r"(a0), "r"(a1), "r"(a2), "r"(a3), "l"(desc), "n"(TB));
}
template <int TB> __device__ __forceinline__ void wgmma_rs_n144(float (&d)[72], uint32_t a0, uint32_t a1, uint32_t a2, uint32_t a3, uint64_t desc) {
  asm volatile("wgmma.mma_async.sync.aligned.m64n144k16.f32.bf16.bf16 "
    "{%0, %1, %2, %3, %4, %5, %6, %7, %8, %9, %10, %11, %12, %13, %14, %15, %16, %17, %18, %19, %20, %21, %22, %23, %24, %25, %26, %27, %28, %29, %30, %31, %32, %33, %34, %35, %36, %37, %38, %39, %40, %41, %42, %43, %44, %45, %46, %47, %48, %49, %50, %51, %52, %53, %54, %55, %56, %57, %58, %59, %60, %61, %62, %63, %64, %65, %66, %67, %68, %69, %70, %71}, "
    "{%72, %73, %74, %75}, %76, 1, 1, 1, %77;"
    : "+f"(d[0]), "+f"(d[1]), "+f"(d[2]), "+f"(d[3]), "+f"(d[4]), "+f"(d[5]), "+f"(d[6]), "+f"(d[7]), "+f"(d[8]), "+f"(d[9]), "+f"(d[10]), "+f"(d[11]), "+f"(d[12]), "+f"(d[13]), "+f"(d[14]), "+f"(d[15]), "+f"(d[16]), "+f"(d[17]), "+f"(d[18]), "+f"(d[19]), "+f"(d[20]), "+f"(d[21]), "+f"(d[22]), "+f"(d[23]), "+f"(d[24]), "+f"(d[25]), "+f"(d[26]), "+f"(d[27]), "+f"(d[28]), "+f"(d[29]), "+f"(d[30]), "+f"(d[31]), "+f"(d[32]), "+f"(d[33]), "+f"(d[34]), "+f"(d[35]), "+f"(d[36]), "+f"(d[37]), "+f"(d[38]), "+f"(d[39]), "+f"(d[40]), "+f"(d[41]), "+f"(d[42]), "+f"(d[43]), "+f"(d[44]), "+f"(d[45]), "+f"(d[46]), "+f"(d[47]), "+f"(d[48]), "+f"(d[49]), "+f"(d[50]), "+f"(d[51]), "+f"(d[52]), "+f"(d[53]), "+f"(d[54]), "+f"(d[55]), "+f"(d[56]), "+f"(d[57]), "+f"(d[58]), "+f"(d[59]), "+f"(d[60]), "+f"(d[61]), "+f"(d[62]), "+f"(d[63]), "+f"(d[64]), "+f"(d[65]), "+f"(d[66]), "+f"(d[67]), "+f"(d[68]), "+f"(d[69]), "+f"(d[70]), "+f"(d[71])
    : "r"(a0), "r"(a1), "r"(a2), "r"(a3), "l"(desc), "n"(TB));
}
template <int TA, int TB> __device__ __forceinline__ void wgmma_ss_n96(float (&d)[48], uint64_t desca, uint64_t descb) {
  asm volatile("wgmma.mma_async.sync.aligned.m64n96k16.f32.bf16.bf16 "
    "{%0, %1, %2, %3, %4, %5, %6, %7, %8, %9, %10, %11, %12, %13, %14, %15, %16, %17, %18, %19, %20, %21, %22, %23, %24, %25, %26, %27, %28, %29, %30, %31, %32, %33, %34, %35, %36, %37, %38, %39, %40, %41, %42, %43, %44, %45, %46, %47}, "
    "%48, %49, 1, 1, 1, %50, %51;"
    : "+f"(d[0]), "+f"(d[1]), "+f"(d[2]), "+f"(d[3]), "+f"(d[4]), "+f"(d[5]), "+f"(d[6]), "+f"(d[7]), "+f"(d[8]), "+f"(d[9]), "+f"(d[10]), "+f"(d[11]), "+f"(d[12]), "+f"(d[13]), "+f"(d[14]), "+f"(d[15]), "+f"(d[16]), "+f"(d[17]), "+f"(d[18]), "+f"(d[19]), "+f"(d[20]), "+f"(d[21]), "+f"(d[22]), "+f"(d[23]), "+f"(d[24]), "+f"(d[25]), "+f"(d[26]), "+f"(d[27]), "+f"(d[28]), "+f"(d[29]), "+f"(d[30]), "+f"(d[31]), "+f"(d[32]), "+f"(d[33]), "+f"(d[34]), "+f"(d[35]), "+f"(d[36]), "+f"(d[37]), "+f"(d[38]), "+f"(d[39]), "+f"(d[40]), "+f"(d[41]), "+f"(d[42]), "+f"(d[43]), "+f"(d[44]), "+f"(d[45]), "+f"(d[46]), "+f"(d[47])
    : "l"(desca), "l"(descb), "n"(TA), "n"(TB));
}


__device__ __forceinline__ void wg_fence() { asm volatile("wgmma.fence.sync.aligned;" ::: "memory"); }
__device__ __forceinline__ void wg_commit() { asm volatile("wgmma.commit_group.sync.aligned;" ::: "memory"); }
template <int N> __device__ __forceinline__ void wg_wait() {
  asm volatile("wgmma.wait_group.sync.aligned %0;" ::"n"(N) : "memory");
}
template <int N> __device__ __forceinline__ void pin(float (&a)[N]) {
#pragma unroll
  for (int i = 0; i < N; i++) asm volatile("" : "+f"(a[i])::"memory");
}
__device__ __forceinline__ uint64_t make_desc(uint32_t addr, uint32_t lbo, uint32_t sbo) {
  uint32_t lo = ((addr & 0x3FFFF) >> 4) | ((lbo >> 4) << 16);
  uint32_t hi = sbo >> 4;
  return ((uint64_t)hi << 32) | lo;
}
__device__ __forceinline__ uint64_t make_desc_sw32(uint32_t addr, uint32_t lbo, uint32_t sbo) {
  return make_desc(addr, lbo, sbo) | (3ull << 62);
}
__device__ __forceinline__ uint64_t desc_add(uint64_t d, uint32_t bytes) { return d + (bytes >> 4); }

__device__ __forceinline__ uint32_t pack_bf16(float lo, float hi) {
  uint32_t r;
  asm("cvt.rn.bf16x2.f32 %0, %1, %2;" : "=r"(r) : "f"(hi), "f"(lo));
  return r;
}
__device__ __forceinline__ uint32_t pack_bf16_v(float lo, float hi) {
  uint32_t r;
  asm volatile("cvt.rn.bf16x2.f32 %0, %1, %2;" : "=r"(r) : "f"(hi), "f"(lo));
  return r;
}
__device__ __forceinline__ uint32_t bf2_add(uint32_t a, uint32_t b) {
  uint32_t r; asm("add.rn.bf16x2 %0, %1, %2;" : "=r"(r) : "r"(a), "r"(b)); return r;
}
__device__ __forceinline__ uint32_t bf2_sub(uint32_t a, uint32_t b) {
  uint32_t r; asm("sub.rn.bf16x2 %0, %1, %2;" : "=r"(r) : "r"(a), "r"(b)); return r;
}
__device__ __forceinline__ uint32_t bf2_fma(uint32_t a, uint32_t b, uint32_t c) {
  uint32_t r; asm("fma.rn.bf16x2 %0, %1, %2, %3;" : "=r"(r) : "r"(a), "r"(b), "r"(c)); return r;
}
__device__ __forceinline__ uint32_t bf2_max(uint32_t a, uint32_t b) {
  uint32_t r; asm("max.bf16x2 %0, %1, %2;" : "=r"(r) : "r"(a), "r"(b)); return r;
}
__device__ __forceinline__ uint32_t bf2_ex2(uint32_t a) {
  uint32_t r; asm("ex2.approx.ftz.bf16x2 %0, %1;" : "=r"(r) : "r"(a)); return r;
}
__device__ __forceinline__ float rcp_approx(float a) {
  float r; asm("rcp.approx.ftz.f32 %0, %1;" : "=f"(r) : "f"(a)); return r;
}
__device__ __forceinline__ uint64_t policy_evict_first() {
  uint64_t p;
  asm("createpolicy.fractional.L2::evict_first.b64 %0, 1.0;" : "=l"(p));
  return p;
}
__device__ __forceinline__ uint4 ldg_stream(const void* p) {
  uint4 v;
  asm volatile("ld.global.L1::no_allocate.L2::cache_hint.v4.b32 {%0,%1,%2,%3}, [%4], %5;"
               : "=r"(v.x), "=r"(v.y), "=r"(v.z), "=r"(v.w) : "l"(p), "l"(policy_evict_first()));
  return v;
}
__device__ __forceinline__ uint4 ldg_cached(const void* p) {
  uint4 v;
  asm volatile("ld.global.nc.v4.b32 {%0,%1,%2,%3}, [%4];"
               : "=r"(v.x), "=r"(v.y), "=r"(v.z), "=r"(v.w) : "l"(p));
  return v;
}
__device__ __forceinline__ void ldsm_x4(uint32_t addr, uint4& v) {
  asm volatile("ldmatrix.sync.aligned.m8n8.x4.shared.b16 {%0,%1,%2,%3}, [%4];"
               : "=r"(v.x), "=r"(v.y), "=r"(v.z), "=r"(v.w) : "r"(addr) : "memory");
}
__device__ __forceinline__ void tma_load_4d(uint32_t dst, const CUtensorMap* map, uint32_t bar, int c1, int c2) {
  asm volatile("cp.async.bulk.tensor.4d.shared::cluster.global.mbarrier::complete_tx::bytes.L2::cache_hint [%0], [%1, {%3, %4, %5, %3}], [%2], %6;"
               ::"r"(dst), "l"(map), "r"(bar), "r"(0), "r"(c1), "r"(c2), "l"(policy_evict_first()) : "memory");
}
__device__ __forceinline__ void tma_prefetch_4d(const CUtensorMap* map, int c1, int c2) {
  asm volatile("cp.async.bulk.prefetch.tensor.4d.L2.global.tile.L2::cache_hint [%0, {%1, %2, %3, %1}], %4;"
               ::"l"(map), "r"(0), "r"(c1), "r"(c2), "l"(policy_evict_first()) : "memory");
}
__device__ __forceinline__ void tma_store_4d(const CUtensorMap* map, uint32_t src, int c1, int c2, int c3) {
  asm volatile("cp.async.bulk.tensor.4d.global.shared::cta.bulk_group [%0, {%2, %3, %4, %5}], [%1];"
               ::"l"(map), "r"(src), "r"(0), "r"(c1), "r"(c2), "r"(c3) : "memory");
  asm volatile("cp.async.bulk.commit_group;" ::: "memory");
}
__device__ __forceinline__ void tma_store_wait_read() { asm volatile("cp.async.bulk.wait_group.read 0;" ::: "memory"); }
__device__ __forceinline__ void bulk_load(uint32_t dst, const void* src, uint32_t bytes, uint32_t bar) {
  asm volatile("cp.async.bulk.shared::cluster.global.mbarrier::complete_tx::bytes [%0], [%1], %2, [%3];"
               ::"r"(dst), "l"(src), "r"(bytes), "r"(bar) : "memory");
}
__device__ __forceinline__ void prefetch_l2(const void* p, uint32_t bytes) {
  asm volatile("cp.async.bulk.prefetch.L2.global.L2::cache_hint [%0], %1, %2;" ::"l"(p), "r"(bytes), "l"(policy_evict_first()) : "memory");
}
__device__ __forceinline__ void stsm_x4(uint32_t addr, uint32_t a, uint32_t b, uint32_t c, uint32_t d) {
  asm volatile("stmatrix.sync.aligned.m8n8.x4.shared.b16 [%0], {%1,%2,%3,%4};"
               ::"r"(addr), "r"(a), "r"(b), "r"(c), "r"(d) : "memory");
}
__device__ __forceinline__ void st_async_v2(uint32_t addr, uint32_t mbar, uint32_t a, uint32_t b) {
  asm volatile("st.async.weak.shared::cluster.mbarrier::complete_tx::bytes.v2.b32 [%0], {%1,%2}, [%3];"
               ::"r"(addr), "r"(a), "r"(b), "r"(mbar) : "memory");
}
__device__ __forceinline__ uint32_t mapa(uint32_t addr, uint32_t rank) {
  uint32_t r; asm("mapa.shared::cluster.u32 %0, %1, %2;" : "=r"(r) : "r"(addr), "r"(rank)); return r;
}
__device__ __forceinline__ void mbar_init(uint32_t bar, uint32_t count) {
  asm volatile("mbarrier.init.shared::cta.b64 [%0], %1;" ::"r"(bar), "r"(count) : "memory");
}
__device__ __forceinline__ void mbar_arrive_remote(uint32_t bar) {
  asm volatile("mbarrier.arrive.relaxed.cluster.shared::cluster.b64 _, [%0];" ::"r"(bar) : "memory");
}
__device__ __forceinline__ void mbar_expect_tx(uint32_t bar, uint32_t bytes) {
  asm volatile("mbarrier.arrive.expect_tx.shared::cta.b64 _, [%0], %1;" ::"r"(bar), "r"(bytes) : "memory");
}
__device__ __forceinline__ void mbar_wait(uint32_t bar, uint32_t parity) {
  asm volatile("{\n.reg .pred p, q;\n.reg .u32 c;\nmov.u32 c, 0;\n"
               "WAIT_LOOP:\n"
               "mbarrier.try_wait.parity.shared::cta.b64 p, [%0], %1;\n"
               "@p bra WAIT_DONE;\n"
               "add.u32 c, c, 1;\n"
               "setp.lt.u32 q, c, 0x1000000;\n"
               "@q bra WAIT_LOOP;\n"
               "trap;\n"
               "WAIT_DONE:\n}\n"
               ::"r"(bar), "r"(parity) : "memory");
}
__device__ __forceinline__ bool elect_one() {
  uint32_t p;
  asm volatile("{\n.reg .pred q;\nelect.sync _|q, 0xffffffff;\nselp.u32 %0, 1, 0, q;\n}\n" : "=r"(p));
  return p != 0;
}
__device__ __forceinline__ void wg_bar(int id) { asm volatile("bar.sync %0, 128;" ::"r"(id) : "memory"); }
__device__ __forceinline__ void fence_async_smem() { asm volatile("fence.proxy.async.shared::cta;" ::: "memory"); }

__device__ __forceinline__ void bias_mask(const uint4 (&b)[4], const uint4 (&mk)[4], uint32_t (&bm)[16]) {
#pragma unroll
  for (int i = 0; i < 4; i++) {
    bm[4 * i] = bf2_fma(mk[i].x, LOG2E_BF16X2, b[i].x);
    bm[4 * i + 1] = bf2_fma(mk[i].y, LOG2E_BF16X2, b[i].y);
    bm[4 * i + 2] = bf2_fma(mk[i].z, LOG2E_BF16X2, b[i].z);
    bm[4 * i + 3] = bf2_fma(mk[i].w, LOG2E_BF16X2, b[i].w);
  }
}
__device__ __forceinline__ void softmax_frag(const float (&s)[32], const uint32_t (&bm)[16],
                                             uint32_t (&pa)[8], uint32_t (&pb)[8]) {
#pragma unroll
  for (int j = 0; j < 8; j++) {
    pa[j] = bf2_add(pack_bf16(s[4 * j], s[4 * j + 1]), bm[j]);
    pb[j] = bf2_add(pack_bf16(s[4 * j + 2], s[4 * j + 3]), bm[8 + j]);
  }
  uint32_t xa = bf2_max(bf2_max(bf2_max(pa[0], pa[1]), bf2_max(pa[2], pa[3])),
                        bf2_max(bf2_max(pa[4], pa[5]), bf2_max(pa[6], pa[7])));
  uint32_t xb = bf2_max(bf2_max(bf2_max(pb[0], pb[1]), bf2_max(pb[2], pb[3])),
                        bf2_max(bf2_max(pb[4], pb[5]), bf2_max(pb[6], pb[7])));
  uint32_t m = bf2_max(__byte_perm(xa, xb, 0x5410), __byte_perm(xa, xb, 0x7632));
  m = bf2_max(m, __shfl_xor_sync(0xffffffffu, m, 1));
  m = bf2_max(m, __shfl_xor_sync(0xffffffffu, m, 2));
  const uint32_t mA = __byte_perm(m, m, 0x1010), mB = __byte_perm(m, m, 0x3232);
#pragma unroll
  for (int j = 0; j < 8; j++) {
    pa[j] = bf2_ex2(bf2_sub(pa[j], mA));
    pb[j] = bf2_ex2(bf2_sub(pb[j], mB));
  }
}
__device__ __forceinline__ void load_bias(const uint4* p, uint4 (&b)[4]) {
#pragma unroll
  for (int i = 0; i < 4; i++) b[i] = ldg_cached(p + 128 * i);
}

constexpr int PREP_PIECES = W_IMG / 16 + 1024;
__global__ void __launch_bounds__(256)
swin_prep_kernel(const __nv_bfloat16* __restrict__ wqkv, const __nv_bfloat16* __restrict__ wo,
                 const __nv_bfloat16* __restrict__ rpb, const int* __restrict__ rp_idx) {
  asm volatile("griddepcontrol.launch_dependents;");
  const int idx = blockIdx.x * 256 + threadIdx.x;
  const int rank = idx / PREP_PIECES;
  int pc = idx - rank * PREP_PIECES;
  if (rank >= 2) return;
  if (pc < (int)(SM_WO / 16)) {
    const int part = pc / 1152, rem = pc - part * 1152;
    const int grp = rem / 384, k = (rem - grp * 384) >> 1, hf = (rem & 1) ^ ((k >> 2) & 1);
    const int sect = (part == 0 || part == 2) ? 192 : (part == 1 || part == 5) ? 384 : 0;
    const int hh = (part == 2 || part == 4 || part == 5) ? 1 : 0;
    uint4 w = __ldg(reinterpret_cast<const uint4*>(wqkv + k * 576 + sect + (2 * rank + hh) * 48 + 16 * grp + 8 * hf));
    if (sect == 0) {
      uint32_t* u = reinterpret_cast<uint32_t*>(&w);
#pragma unroll
      for (int c = 0; c < 4; c++)
        u[c] = pack_bf16(__uint_as_float(u[c] << 16) * QSCALE, __uint_as_float(u[c] & 0xffff0000u) * QSCALE);
    }
    g_wimg[rank][pc] = w;
  } else if (pc < (int)(W_IMG / 16)) {
    const int q0 = pc - SM_WO / 16;
    const int half = q0 / 1152, rem = q0 - half * 1152;
    const int grp = rem / 192, k = (rem - grp * 192) >> 1, hf = (rem & 1) ^ ((k >> 2) & 1);
    int row = 96 * rank + k;
    if (half) {
      const int p = k >> 4, tt = (k >> 2) & 3, i = (k >> 1) & 1;
      row = 96 * (rank ^ 1) + 16 * p + 8 * i + 2 * tt + (k & 1);
    }
    g_wimg[rank][pc] = __ldg(reinterpret_cast<const uint4*>(wo + row * CH + 96 * rank + 16 * grp + 8 * hf));
  } else {
    pc -= W_IMG / 16;
    const int hh = pc >> 9, sel = (pc >> 8) & 1, u = (pc >> 7) & 1, wt = pc & 127;
    const int w4 = wt >> 5, gg = (wt & 31) >> 2, tt = wt & 3;
    const int row = 8 * ((gg >> 1) + 4 * (w4 >> 1)) + 4 * (w4 & 1) + (gg & 1) + 2 * sel;
    const int4* p = reinterpret_cast<const int4*>(rp_idx + row * 64 + 8 * (tt + 4 * u));
    if ((threadIdx.x & 31) < 15) asm volatile("prefetch.global.L1 [%0];" ::"l"(rpb + (threadIdx.x & 31) * 64));
    const int4 i0 = __ldg(p), i1 = __ldg(p + 1);
    const int head = 2 * rank + hh;
    auto bv = [&](int i) { return __bfloat162float(rpb[i * 4 + head]) * LOG2E; };
    g_bias[rank][pc] = make_uint4(pack_bf16(bv(i0.x), bv(i0.y)), pack_bf16(bv(i0.z), bv(i0.w)),
                                  pack_bf16(bv(i1.x), bv(i1.y)), pack_bf16(bv(i1.z), bv(i1.w)));
  }
}

__global__ void __cluster_dims__(2, 1, 1) __launch_bounds__(NTHREADS, 1)
swin_window_attn_kernel(const __grid_constant__ CUtensorMap xmap, const __grid_constant__ CUtensorMap ymap,
                        const __nv_bfloat16* __restrict__ mask) {
  extern __shared__ __align__(1024) uint8_t smem[];
  const uint32_t sbase = (uint32_t)__cvta_generic_to_shared(smem);
  const int tid = threadIdx.x;
  const int wg = __shfl_sync(0xffffffffu, tid >> 7, 0);
  const int wtid = tid & 127, lane = tid & 31;
  const int warp = __shfl_sync(0xffffffffu, wtid >> 5, 0);
  const int g = lane >> 2, t = lane & 3;
  uint32_t crank;
  asm("mov.u32 %0, %%cluster_ctarank;" : "=r"(crank));
  const int ncl = gridDim.x >> 1;
  const int cl = blockIdx.x >> 1;

  const int th = (g >> 1) + 4 * (warp >> 1);
  const int tw = 4 * (warp & 1) + (g & 1);
  const int wstride = ncl * NWG;
  int win = wg * ncl + cl;

  const uint32_t bar_rdy = sbase + SM_BAR + wg * 32;
  const uint32_t bar_dat = bar_rdy + 16;
  const uint32_t bar_x0 = sbase + SM_BAR + 96;
  const uint32_t x_quad = sbase + SM_X + warp * X_QUAD;
  auto quad_coords = [&](int w, int& y, int& x) {
    const int wi = w / 48, wj = w - wi * 48;
    y = wi * 8 + 4 + 4 * (warp >> 1);
    x = wj * 8 + 4 + 4 * (warp & 1);
    if (y >= IMG) y -= IMG;
    if (x >= IMG) x -= IMG;
  };
  auto issue_x = [&](int w, int dst_wg) {
    int y, x;
    quad_coords(w, y, x);
    const uint32_t bar = bar_x0 + (dst_wg * 4 + warp) * 8;
    mbar_expect_tx(bar, X_QUAD);
    tma_load_4d(x_quad, &xmap, bar, y, x);
    if ((warp & 1) == crank && w + PF_DIST * ncl < NWIN) {
      quad_coords(w + PF_DIST * ncl, y, x);
      tma_prefetch_4d(&xmap, y, x);
    }
  };

  const uint32_t bar_w = bar_x0 + 96;
  const uint32_t wgbuf = sbase + SM_WG + wg * WG_BYTES;
  const uint64_t d_wqkv = make_desc_sw32(sbase + SM_WQKV, 6144, 256);
  const uint64_t d_wo = make_desc_sw32(sbase + SM_WO, 3072, 256);
  const uint64_t d_k = make_desc(wgbuf, 1024, 128);
  const uint64_t d_v = make_desc(wgbuf, 128, 1024);
  const uint64_t d_ex = make_desc_sw32(wgbuf, 16, 256);
  if (tid == 0) {
#pragma unroll
    for (int i = 0; i < NWG; i++) {
      mbar_init(sbase + SM_BAR + i * 32, 4);
      mbar_init(sbase + SM_BAR + i * 32 + 8, 4);
      mbar_init(sbase + SM_BAR + i * 32 + 16, 1);
      mbar_init(sbase + SM_BAR + i * 32 + 24, 1);
    }
#pragma unroll
    for (int i = 0; i < 4 * NWG; i++) mbar_init(bar_x0 + i * 8, 1);
    mbar_init(bar_w, 1);
    asm volatile("fence.mbarrier_init.release.cluster;" ::: "memory");
    fence_async_smem();
  }
  *reinterpret_cast<uint2*>(smem + SM_WG + wg * WG_BYTES + OFF_ONES + wtid * 8) = make_uint2(0x3F803F80u, 0x3F803F80u);
  fence_async_smem();
  __syncthreads();
  asm volatile("barrier.cluster.arrive.relaxed.aligned;" ::: "memory");
  if (wg == 0 && lane == 0 && win < NWIN) issue_x(win, 0);
  asm volatile("griddepcontrol.wait;" ::: "memory");
  if (tid == 0) {
    mbar_expect_tx(bar_w, W_IMG);
    const uint8_t* img = reinterpret_cast<const uint8_t*>(g_wimg[crank]);
#pragma unroll
    for (int i = 0; i < 3; i++) bulk_load(sbase + i * (W_IMG / 3), img + i * (W_IMG / 3), W_IMG / 3, bar_w);
  }
  asm volatile("barrier.cluster.wait.acquire.aligned;" ::: "memory");

  auto keep = [&](uint32_t v) { return (uint32_t)__shfl_sync(0xffffffffu, v, lane); };
  const int mi = lane >> 3, r8 = lane & 7;
  const uint32_t t_st = wgbuf + (mi >> 1) * 1024 + (2 * warp + (mi & 1)) * 128 + r8 * 16;
  const uint32_t ex_remote = mapa(wgbuf + (16 * warp + g) * 32 + (((t >> 1) ^ (g >> 2)) << 4) + (t & 1) * 8, crank ^ 1);
  const uint32_t dat_remote = mapa(bar_dat, crank ^ 1);
  const uint32_t rdy_remote = mapa(bar_rdy, crank ^ 1);
  const uint4* bias_ptr = &g_bias[crank][wtid];
  const uint32_t y_quad = wgbuf + warp * 3072;
  const uint32_t y_st = [&] {
    const int gg = lane & 7, sel = (lane >> 3) & 1, chi = lane >> 4;
    const int r = (2 * sel + (gg & 1)) * 4 + (gg >> 1);
    return y_quad + r * 64 + ((chi ^ ((r >> 1) & 3)) << 4);
  }();

  const uint32_t x_ld = [&] {
    const int gg = lane & 7, sel = (lane >> 3) & 1, khi = lane >> 4;
    const int r = (2 * sel + (gg & 1)) * 4 + (gg >> 1);
    return x_quad + r * 128 + ((khi ^ (r & 7)) << 4);
  }();
  const uint32_t bar_x = bar_x0 + (wg * 4 + warp) * 8;
  const int next_wg = wg == NWG - 1 ? 0 : wg + 1;
  const uint32_t mask_off = keep(((8 * th + tw) * 64 + 8 * t) * 2);

  uint4 xa[12];
  auto load_x_frags = [&](bool valid, uint32_t par) {
    if (valid) mbar_wait(bar_x, par);
#pragma unroll
    for (int s = 0; s < 12; s++) ldsm_x4((x_ld ^ ((s & 3) << 5)) + (s >> 2) * 2048, xa[s]);
  };
  load_x_frags(win < NWIN, 0);

  uint4 b0[4];
  load_bias(bias_ptr, b0);
  mbar_wait(bar_w, 0);
  uint32_t parity = 0;
  for (; win < NWIN; win += wstride, parity ^= 1) {
    uint4 mk[4];
    {
      float acc[72];
      wg_fence();
#pragma unroll
      for (int s = 0; s < 12; s++) {
        if (s == 0) wgmma_rs_n144_init<1>(acc, xa[s].x, xa[s].y, xa[s].z, xa[s].w, desc_add(d_wqkv, s * 512));
        else        wgmma_rs_n144<1>(acc, xa[s].x, xa[s].y, xa[s].z, xa[s].w, desc_add(d_wqkv, s * 512));
      }
      wg_commit();
      if (win + ncl < NWIN && elect_one()) issue_x(win + ncl, next_wg);
      if (warp == 0 && crank == 0 && win + wstride < NWIN && elect_one()) prefetch_l2(mask + (size_t)(win + wstride) * 4096, 8192);
      tma_store_wait_read();
      wg_bar(1 + wg);
      const __nv_bfloat16* mp = reinterpret_cast<const __nv_bfloat16*>(reinterpret_cast<const uint8_t*>(mask + (size_t)win * 4096) + mask_off);
      mk[0] = ldg_stream(mp);
      mk[1] = ldg_stream(mp + 32);
      mk[2] = ldg_stream(mp + 128);
      mk[3] = ldg_stream(mp + 160);
      wg_wait<0>();
      pin(acc);
#pragma unroll
      for (int j = 0; j < 18; j += 2) {
        const uint32_t off = (j < 6 ? OFF_K0 : j < 12 ? OFF_V0 : OFF_K1) + (j % 6) * 1024;
        stsm_x4(t_st + off, pack_bf16(acc[4 * j], acc[4 * j + 1]), pack_bf16(acc[4 * j + 2], acc[4 * j + 3]),
                pack_bf16(acc[4 * j + 4], acc[4 * j + 5]), pack_bf16(acc[4 * j + 6], acc[4 * j + 7]));
      }
      fence_async_smem();
    }
    float s0[32], s1[32];
    uint32_t v1[12];
    uint32_t bm[16];
    {
      float acc[72];
      wg_fence();
#pragma unroll
      for (int s = 0; s < 12; s++) {
        if (s == 0) wgmma_rs_n144_init<1>(acc, xa[s].x, xa[s].y, xa[s].z, xa[s].w, desc_add(d_wqkv, WQKV_HEAD + s * 512));
        else        wgmma_rs_n144<1>(acc, xa[s].x, xa[s].y, xa[s].z, xa[s].w, desc_add(d_wqkv, WQKV_HEAD + s * 512));
      }
      wg_commit();
      wg_bar(1 + wg);
      wg_wait<0>();
      pin(acc);
      uint32_t qa[12], qb[12];
#pragma unroll
      for (int j = 0; j < 12; j++) {
        qa[j] = pack_bf16(acc[4 * j], acc[4 * j + 1]);
        qb[j] = pack_bf16(acc[4 * j + 2], acc[4 * j + 3]);
      }
#pragma unroll
      for (int j = 0; j < 12; j++) v1[j] = pack_bf16(acc[48 + 2 * j], acc[48 + 2 * j + 1]);
      wg_fence();
#pragma unroll
      for (int k = 0; k < 3; k++) {
        if (k == 0) wgmma_rs_n64_init<0>(s0, qa[0], qb[0], qa[1], qb[1], desc_add(d_k, OFF_K0));
        else        wgmma_rs_n64<0>(s0, qa[2 * k], qb[2 * k], qa[2 * k + 1], qb[2 * k + 1], desc_add(d_k, OFF_K0 + k * 2048));
      }
      wg_commit();
#pragma unroll
      for (int k = 0; k < 3; k++) {
        if (k == 0) wgmma_rs_n64_init<0>(s1, qa[6], qb[6], qa[7], qb[7], desc_add(d_k, OFF_K1));
        else        wgmma_rs_n64<0>(s1, qa[6 + 2 * k], qb[6 + 2 * k], qa[7 + 2 * k], qb[7 + 2 * k], desc_add(d_k, OFF_K1 + k * 2048));
      }
      wg_commit();
      bias_mask(b0, mk, bm);
      wg_wait<1>();
      pin(s0);
    }
    uint32_t pa[8], pb[8];
    float o0[28];
    wg_bar(1 + wg);
#pragma unroll
    for (int j = 0; j < 3; j++) stsm_x4(t_st + OFF_K0 + j * 2048, v1[4 * j], v1[4 * j + 1], v1[4 * j + 2], v1[4 * j + 3]);
    fence_async_smem();
    uint4 b1[4];
    load_bias(bias_ptr + 512, b1);
    softmax_frag(s0, bm, pa, pb);
    wg_fence();
#pragma unroll
    for (int k = 0; k < 4; k++) {
      if (k == 0) wgmma_rs_n56_init<1>(o0, pa[0], pb[0], pa[1], pb[1], desc_add(d_v, OFF_V0));
      else        wgmma_rs_n56<1>(o0, pa[2 * k], pb[2 * k], pa[2 * k + 1], pb[2 * k + 1], desc_add(d_v, OFF_V0 + k * 256));
    }
    wg_commit();
    bias_mask(b1, mk, bm);
    wg_wait<1>();
    pin(s1);
    if (elect_one()) mbar_arrive_remote(rdy_remote);
    if (warp == 0 && elect_one()) {
      mbar_expect_tx(bar_dat, 64 * 48 * 2);
      mbar_expect_tx(bar_dat + 8, 64 * 48 * 2);
    }
    uint32_t pc[8], pd[8];
    softmax_frag(s1, bm, pc, pd);
    wg_wait<0>();
    pin(o0);
    if (elect_one()) mbar_arrive_remote(rdy_remote + 8);
    wg_bar(1 + wg);
    float o1[28];
    wg_fence();
#pragma unroll
    for (int k = 0; k < 4; k++) {
      if (k == 0) wgmma_rs_n56_init<1>(o1, pc[0], pd[0], pc[1], pd[1], desc_add(d_v, OFF_ONES));
      else        wgmma_rs_n56<1>(o1, pc[2 * k], pd[2 * k], pc[2 * k + 1], pd[2 * k + 1], desc_add(d_v, OFF_ONES + k * 256));
    }
    wg_commit();
    uint32_t oa[12], ob[12], sa[12], sb[12];
    float acc[48];
    {
      const float ra = rcp_approx(o0[24]), rb = rcp_approx(o0[26]);
#pragma unroll
      for (int j = 0; j < 6; j++) {
        const float a0 = o0[4 * j] * ra, a1 = o0[4 * j + 1] * ra, c0 = o0[4 * j + 2] * rb, c1 = o0[4 * j + 3] * rb;
        oa[j] = pack_bf16(a0, a1);
        ob[j] = pack_bf16(c0, c1);
        sa[j] = pack_bf16_v(a0, a1);
        sb[j] = pack_bf16_v(c0, c1);
      }
    }
    mbar_wait(bar_rdy, parity);
#pragma unroll
    for (int p = 0; p < 3; p++) {
      st_async_v2(ex_remote + OFF_K1 + p * 2048, dat_remote, sa[2 * p], sa[2 * p + 1]);
      st_async_v2(ex_remote + OFF_K1 + p * 2048 + 256, dat_remote, sb[2 * p], sb[2 * p + 1]);
    }
    wg_fence();
#pragma unroll
    for (int s = 0; s < 3; s++) {
      if (s == 0) wgmma_rs_n96_init<1>(acc, oa[0], ob[0], oa[1], ob[1], d_wo);
      else        wgmma_rs_n96<1>(acc, oa[2 * s], ob[2 * s], oa[2 * s + 1], ob[2 * s + 1], desc_add(d_wo, s * 512));
    }
    wg_commit();
    wg_wait<1>();
    pin(o1);
    {
      const float ra = rcp_approx(o1[0]), rb = rcp_approx(o1[2]);
#pragma unroll
      for (int j = 0; j < 6; j++) {
        const float a0 = o1[4 + 4 * j] * ra, a1 = o1[4 + 4 * j + 1] * ra, c0 = o1[4 + 4 * j + 2] * rb, c1 = o1[4 + 4 * j + 3] * rb;
        oa[6 + j] = pack_bf16(a0, a1);
        ob[6 + j] = pack_bf16(c0, c1);
        sa[6 + j] = pack_bf16_v(a0, a1);
        sb[6 + j] = pack_bf16_v(c0, c1);
      }
    }
    mbar_wait(bar_rdy + 8, parity);
#pragma unroll
    for (int p = 0; p < 3; p++) {
      st_async_v2(ex_remote + OFF_V0 + p * 2048, dat_remote + 8, sa[6 + 2 * p], sa[6 + 2 * p + 1]);
      st_async_v2(ex_remote + OFF_V0 + p * 2048 + 256, dat_remote + 8, sb[6 + 2 * p], sb[6 + 2 * p + 1]);
    }
    wg_fence();
#pragma unroll
    for (int s = 3; s < 6; s++)
      wgmma_rs_n96<1>(acc, oa[2 * s], ob[2 * s], oa[2 * s + 1], ob[2 * s + 1], desc_add(d_wo, s * 512));
    wg_commit();
    mbar_wait(bar_dat, parity);
    fence_async_smem();
    wg_fence();
#pragma unroll
    for (int s = 0; s < 3; s++)
      wgmma_ss_n96<0, 1>(acc, desc_add(d_ex, s * 2048), desc_add(d_wo, WO_HALF + s * 512));
    wg_commit();
    mbar_wait(bar_dat + 8, parity);
    fence_async_smem();
    wg_fence();
#pragma unroll
    for (int s = 3; s < 6; s++)
      wgmma_ss_n96<0, 1>(acc, desc_add(d_ex, s * 2048), desc_add(d_wo, WO_HALF + s * 512));
    wg_commit();
    load_x_frags(win + wstride < NWIN, parity ^ 1);
    wg_wait<0>();
    pin(acc);
    wg_bar(1 + wg);
#pragma unroll
    for (int j = 0; j < 12; j += 2)
      stsm_x4((y_st ^ ((j & 2) << 4)) + (j >> 2) * 1024, pack_bf16(acc[4 * j], acc[4 * j + 1]), pack_bf16(acc[4 * j + 2], acc[4 * j + 3]),
              pack_bf16(acc[4 * j + 4], acc[4 * j + 5]), pack_bf16(acc[4 * j + 6], acc[4 * j + 7]));
    fence_async_smem();
    __syncwarp();
    if (elect_one()) {
      const int wi = win / 48, wj = win - wi * 48;
      int y = wi * 8 + 4 + 4 * (warp >> 1), x = wj * 8 + 4 + 4 * (warp & 1);
      if (y >= IMG) y -= IMG;
      if (x >= IMG) x -= IMG;
      tma_store_4d(&ymap, y_quad, y, x, 3 * crank);
    }
  }
  tma_store_wait_read();
  asm volatile("barrier.cluster.arrive.relaxed.aligned;\nbarrier.cluster.wait.aligned;" ::: "memory");
}

}

extern "C" void kernel_launch(void* const* d_in, const int* in_sizes, int n_in, void* d_out, int out_size) {
  (void)in_sizes; (void)n_in; (void)out_size;
  typedef CUresult (*EncodeFn)(CUtensorMap*, CUtensorMapDataType, cuuint32_t, void*, const cuuint64_t*, const cuuint64_t*,
                               const cuuint32_t*, const cuuint32_t*, CUtensorMapInterleave, CUtensorMapSwizzle,
                               CUtensorMapL2promotion, CUtensorMapFloatOOBfill);
  static int grid = 0;
  static EncodeFn encode = nullptr;
  if (grid == 0) {
    int dev = 0, sms = 0;
    cudaGetDevice(&dev);
    cudaDeviceGetAttribute(&sms, cudaDevAttrMultiProcessorCount, dev);
    cudaFuncSetAttribute(swin::swin_window_attn_kernel, cudaFuncAttributeMaxDynamicSharedMemorySize, swin::SM_TOTAL);
    void* fn = nullptr;
    cudaDriverEntryPointQueryResult qr;
    cudaGetDriverEntryPoint("cuTensorMapEncodeTiled", &fn, cudaEnableDefault, &qr);
    encode = (EncodeFn)fn;
    grid = sms & ~1;
  }
  CUtensorMap xmap;
  const cuuint64_t dims[4] = {64, 384, 384, 3};
  const cuuint64_t strides[3] = {384ull * 384ull, 384, 128};
  const cuuint32_t box[4] = {64, 4, 4, 3};
  const cuuint32_t estr[4] = {1, 1, 1, 1};
  encode(&xmap, CU_TENSOR_MAP_DATA_TYPE_BFLOAT16, 4, d_in[0], dims, strides, box, estr, CU_TENSOR_MAP_INTERLEAVE_NONE,
         CU_TENSOR_MAP_SWIZZLE_128B, CU_TENSOR_MAP_L2_PROMOTION_NONE, CU_TENSOR_MAP_FLOAT_OOB_FILL_NONE);
  CUtensorMap ymap;
  const cuuint64_t ydims[4] = {32, 384, 384, 6};
  const cuuint64_t ystrides[3] = {384ull * 384ull, 384, 64};
  const cuuint32_t ybox[4] = {32, 4, 4, 3};
  encode(&ymap, CU_TENSOR_MAP_DATA_TYPE_BFLOAT16, 4, d_out, ydims, ystrides, ybox, estr, CU_TENSOR_MAP_INTERLEAVE_NONE,
         CU_TENSOR_MAP_SWIZZLE_64B, CU_TENSOR_MAP_L2_PROMOTION_NONE, CU_TENSOR_MAP_FLOAT_OOB_FILL_NONE);
  swin::swin_prep_kernel<<<(2 * swin::PREP_PIECES + 255) / 256, 256, 0, cudaStreamPerThread>>>(
      (const __nv_bfloat16*)d_in[1], (const __nv_bfloat16*)d_in[2], (const __nv_bfloat16*)d_in[3], (const int*)d_in[4]);
  cudaLaunchConfig_t cfg = {};
  cfg.gridDim = dim3(grid);
  cfg.blockDim = dim3(swin::NTHREADS);
  cfg.dynamicSmemBytes = swin::SM_TOTAL;
  cfg.stream = cudaStreamPerThread;
  cudaLaunchAttribute attr[1];
  attr[0].id = cudaLaunchAttributeProgrammaticStreamSerialization;
  attr[0].val.programmaticStreamSerializationAllowed = 1;
  cfg.attrs = attr;
  cfg.numAttrs = 1;
  cudaLaunchKernelEx(&cfg, swin::swin_window_attn_kernel, xmap, ymap, (const __nv_bfloat16*)d_in[5]);
}
```
